```python
import torch

def _softmax(x, axis=-1):
    return torch.softmax(x, dim=axis)
def _gelu(x):
    return torch.nn.functional.gelu(x, approximate="tanh")
def _silu(x):
    return torch.nn.functional.silu(x)
def _sigmoid(x):
    return torch.sigmoid(x)
def _layernorm(x, axis=-1, eps=1e-5):
    m = x.mean(dim=axis, keepdim=True)
    v = x.var(dim=axis, keepdim=True, unbiased=False)
    return (x - m) / torch.sqrt(v + eps)
def _scatter_add(tgt, idx, src, axis=0):
    return tgt.clone().index_add_(axis, idx, src)
def _segment_sum(src, seg, n):
    out = torch.zeros((n,) + src.shape[1:], dtype=src.dtype)
    return out.index_add_(0, seg, src)
def _pad(x, pw):
    flat = tuple(v for pair in reversed(pw) for v in pair)
    return torch.nn.functional.pad(x, flat)

kernel_name = 'standalone__gqa_block_cached__near_ridge'

def setup_inputs():

    _w = (lambda a: (lambda t: t.to(torch.bfloat16) if t.is_floating_point() else t)(torch.as_tensor(a)))
    B, Sq, D = 32, 96, 640
    Hq, Hkv, Sk, Dh = 32, 32, 512, 128
    assert Hq % Hkv == 0, (Hq, Hkv)
    return {
        "x": _w((lambda *s: torch.randn(*s, dtype=torch.bfloat16) * 0.8)(B, Sq, D)),
        "k_cache": _w((lambda *s: torch.randn(*s, dtype=torch.bfloat16) * 0.8)(B, Hkv, Sk, Dh)),
        "v_cache": _w((lambda *s: torch.randn(*s, dtype=torch.bfloat16) * 0.05)(B, Hkv, Sk, Dh)),
        "wq": _w((lambda *s: torch.randn(*s, dtype=torch.bfloat16) * 0.8)(D, Hq * Dh) * (D ** -0.5)),
        "wo": _w((lambda *s: torch.randn(*s, dtype=torch.bfloat16) * 0.05)(Hq * Dh, D) * ((Hq * Dh) ** -0.5)),
    }

def reference(x, k_cache, v_cache, wq, wo):
    B, Sq, D = x.shape
    Hq, Dh = 32, 128
    Hkv = k_cache.shape[1]
    rep = Hq // Hkv
    q = (lambda x, *d: x.permute(*d))((x @ wq).reshape(B, Sq, Hq, Dh), 0, 2, 1, 3)
    k = (lambda x, n, axis: torch.repeat_interleave(x, n, dim=axis))(k_cache, rep, axis=1)
    v = (lambda x, n, axis: torch.repeat_interleave(x, n, dim=axis))(v_cache, rep, axis=1)
    scores = torch.einsum("bhqd,bhkd->bhqk", q, k) * (Dh ** -0.5)
    p = _softmax(scores, axis=-1)
    o = torch.einsum("bhqk,bhkd->bhqd", p, v)
    return (lambda x, *d: x.permute(*d))(o, 0, 2, 1, 3).reshape(B, Sq, Hq * Dh) @ wo
```

```cpp
#include <cuda_runtime.h>
#include <cuda.h>
#include <cuda_bf16.h>
#include <stdint.h>
#include <type_traits>

namespace {

constexpr int NB = 32, SQ = 96, DM = 640, NH = 32, SK = 512, DH = 128;
constexpr int NG = 4;
constexpr int NSTEP = NH / NG;
constexpr int NCTA = NB * NG;
constexpr int OCOLS = DM / NG;

#define KVI 2
#define KVPF 4
constexpr int KV_SLOTS = 5, KV_BYTES = 16384, KV_INFLIGHT = KVI;
constexpr int PR_SLOTS = 3, PR_BYTES = 32768;
constexpr int TILE = 12288;
constexpr int OFF_KV = 0;
constexpr int OFF_PR = OFF_KV + KV_SLOTS * KV_BYTES;
constexpr int OFF_Q = OFF_PR + PR_SLOTS * PR_BYTES;
constexpr int OFF_P = OFF_Q + 2 * TILE;
constexpr int OFF_RED = OFF_P;
constexpr int OFF_REFB = OFF_P + 2 * TILE;
constexpr int OFF_ONES = OFF_REFB + 96 * 16;
constexpr int OFF_INV = OFF_ONES + 128;
constexpr int OFF_BAR = OFF_INV + 96 * 4;
constexpr int BAR_KVF = OFF_BAR, BAR_KVE = BAR_KVF + 8 * KV_SLOTS;
constexpr int BAR_PQF = BAR_KVE + 8 * KV_SLOTS, BAR_POF = BAR_PQF + 8 * PR_SLOTS, BAR_PE = BAR_POF + 8 * PR_SLOTS;
constexpr int BAR_QF = BAR_PE + 8 * PR_SLOTS, BAR_QE = BAR_QF + 8, BAR_OF = BAR_QE + 8, BAR_OE = BAR_OF + 8;
constexpr int OFF_CNT = BAR_OE + 8;
constexpr int SMEM_BYTES = OFF_CNT + 32;
constexpr uint32_t SB0 = 1024;
static_assert(SMEM_BYTES <= 232448, "smem");

constexpr float SM_SCALE_LOG2 = 0.08838834764831845f * 1.4426950408889634f;
constexpr float SUM_LIMIT = 1.152921504606847e18f;
constexpr float REF_LIMIT = 4096.f;

__device__ __align__(1024) uint8_t g_oscr[2 * NCTA * 2 * TILE];
__device__ unsigned g_prog[NCTA * 32];
__device__ unsigned g_cons[NCTA * 32];

#define TL(role, idx)
#define TC(role, idx)

__device__ __forceinline__ uint32_t smem_u32(const void* p) { return (uint32_t)__cvta_generic_to_shared(p); }
__device__ __forceinline__ void mbar_init(uint32_t bar, uint32_t cnt) { asm volatile("mbarrier.init.shared::cta.b64 [%0], %1;" :: "r"(bar), "r"(cnt) : "memory"); }
__device__ __forceinline__ void mbar_expect_tx(uint32_t bar, uint32_t bytes) { asm volatile("mbarrier.arrive.expect_tx.shared::cta.b64 _, [%0], %1;" :: "r"(bar), "r"(bytes) : "memory"); }
__device__ __forceinline__ void mbar_arrive(uint32_t bar) { asm volatile("mbarrier.arrive.shared::cta.b64 _, [%0];" :: "r"(bar) : "memory"); }
__device__ __forceinline__ void mbar_wait(uint32_t bar, uint32_t parity) {
    asm volatile("{\n.reg .pred p;\n.reg .u32 c;\n"
                 "mbarrier.try_wait.parity.shared::cta.b64 p, [%0], %1;\n"
                 "@p bra LAB_DONE;\n"
                 "mov.u32 c, 0;\n"
                 "LAB_WAIT:\n"
                 "mbarrier.try_wait.parity.shared::cta.b64 p, [%0], %1;\n"
                 "@p bra LAB_DONE;\n"
                 "add.u32 c, c, 1;\nsetp.lt.u32 p, c, 0x1000000;\n"
                 "@p bra LAB_WAIT;\n"
                 "trap;\n"
                 "LAB_DONE:\n}" :: "r"(bar), "r"(parity) : "memory");
}
__device__ __forceinline__ bool mbar_test(uint32_t bar, uint32_t parity) {
    uint32_t r;
    asm volatile("{\n.reg .pred p;\nmbarrier.test_wait.parity.shared::cta.b64 p, [%1], %2;\nselp.u32 %0, 1, 0, p;\n}" : "=r"(r) : "r"(bar), "r"(parity) : "memory");
    return r != 0;
}
__device__ __forceinline__ void warp_arrive(uint32_t bar) {
    __syncwarp();
    if ((threadIdx.x & 31) == 0) mbar_arrive(bar);
}
__device__ __forceinline__ void warp_arrive_pair(uint32_t bar) {
    __syncwarp();
    const uint32_t lane = threadIdx.x & 31;
    if (lane < 2) asm volatile("{\n.reg .b32 ra;\nmapa.shared::cluster.u32 ra, %0, %1;\nmbarrier.arrive.shared::cluster.b64 _, [ra];\n}" :: "r"(bar), "r"(lane) : "memory");
}
__device__ __forceinline__ void cluster_wait() { asm volatile("barrier.cluster.wait.acquire.aligned;" ::: "memory"); }
__device__ __forceinline__ void cnt_wait(uint32_t addr, int target) {
    for (unsigned c = 0;; c++) {
        int v;
        asm volatile("ld.acquire.cta.shared.u32 %0, [%1];" : "=r"(v) : "r"(addr) : "memory");
        if (v >= target) return;
        __nanosleep(40);
        if (c > 0x4000000u) __trap();
    }
}
__device__ __forceinline__ void flag_set_relaxed(unsigned* p, unsigned v) { asm volatile("st.relaxed.gpu.global.u32 [%0], %1;" :: "l"(p), "r"(v) : "memory"); }
__device__ __forceinline__ void flag_set(unsigned* p, unsigned v) { asm volatile("st.release.gpu.global.u32 [%0], %1;" :: "l"(p), "r"(v) : "memory"); }
__device__ __forceinline__ void fence_async_smem() { asm volatile("fence.proxy.async.shared::cta;" ::: "memory"); }
__device__ __forceinline__ void bar_sync(int id) { asm volatile("bar.sync %0, 128;" :: "r"(id) : "memory"); }
__device__ __forceinline__ bool bar_or(int id, bool v) {
    uint32_t r;
    asm volatile("{\n.reg .pred p, q;\nsetp.ne.u32 p, %2, 0;\nbar.red.or.pred q, %1, 128, p;\nselp.u32 %0, 1, 0, q;\n}" : "=r"(r) : "r"(id), "r"((uint32_t)v) : "memory");
    return r != 0;
}
__device__ __forceinline__ void tma_2d(uint32_t dst, const CUtensorMap* m, int c0, int c1, uint32_t bar) {
    asm volatile("cp.async.bulk.tensor.2d.shared::cluster.global.mbarrier::complete_tx::bytes [%0], [%1, {%3, %4}], [%2];"
                 :: "r"(dst), "l"((uint64_t)m), "r"(bar), "r"(c0), "r"(c1) : "memory");
}
__device__ __forceinline__ void tma_2d_mc(uint32_t dst, const CUtensorMap* m, int c0, int c1, uint32_t bar) {
    asm volatile("cp.async.bulk.tensor.2d.shared::cluster.global.mbarrier::complete_tx::bytes.multicast::cluster [%0], [%1, {%3, %4}], [%2], %5;"
                 :: "r"(dst), "l"((uint64_t)m), "r"(bar), "r"(c0), "r"(c1), "h"((uint16_t)3) : "memory");
}
__device__ __forceinline__ void tma_prefetch_2d(const CUtensorMap* m, int c0, int c1) {
    asm volatile("cp.async.bulk.prefetch.tensor.2d.L2.global [%0, {%1, %2}];" :: "l"((uint64_t)m), "r"(c0), "r"(c1) : "memory");
}
__device__ __forceinline__ void tma_3d_hint(uint32_t dst, const CUtensorMap* m, int c0, int c1, int c2, uint32_t bar, uint64_t pol) {
    asm volatile("cp.async.bulk.tensor.3d.shared::cluster.global.mbarrier::complete_tx::bytes.L2::cache_hint [%0], [%1, {%3, %4, %5}], [%2], %6;"
                 :: "r"(dst), "l"((uint64_t)m), "r"(bar), "r"(c0), "r"(c1), "r"(c2), "l"(pol) : "memory");
}
__device__ __forceinline__ void tma_store_2d(const CUtensorMap* m, int c0, int c1, uint32_t src) {
    asm volatile("cp.async.bulk.tensor.2d.global.shared::cta.bulk_group [%0, {%2, %3}], [%1];"
                 :: "l"((uint64_t)m), "r"(src), "r"(c0), "r"(c1) : "memory");
}
__device__ __forceinline__ void bulk_load(uint32_t dst, const void* src, uint32_t bytes, uint32_t bar) {
    asm volatile("cp.async.bulk.shared::cluster.global.mbarrier::complete_tx::bytes [%0], [%1], %2, [%3];"
                 :: "r"(dst), "l"((uint64_t)src), "r"(bytes), "r"(bar) : "memory");
}
__device__ __forceinline__ void bulk_store(void* dst, uint32_t src, uint32_t bytes) {
    asm volatile("cp.async.bulk.global.shared::cta.bulk_group [%0], [%1], %2;" :: "l"((uint64_t)dst), "r"(src), "r"(bytes) : "memory");
}
__device__ __forceinline__ void l2_prefetch(const void* p, uint32_t bytes) {
    asm volatile("cp.async.bulk.prefetch.L2.global [%0], %1;" :: "l"((uint64_t)p), "r"(bytes) : "memory");
}
__device__ __forceinline__ void wg_fence() { asm volatile("wgmma.fence.sync.aligned;" ::: "memory"); }
__device__ __forceinline__ void wg_commit() { asm volatile("wgmma.commit_group.sync.aligned;" ::: "memory"); }
template <int N> __device__ __forceinline__ void wg_wait() { asm volatile("wgmma.wait_group.sync.aligned %0;" :: "n"(N) : "memory"); }
__device__ __forceinline__ float ex2v(float x) { float y; asm volatile("ex2.approx.ftz.f32 %0, %1;" : "=f"(y) : "f"(x)); return y; }
__device__ __forceinline__ uint32_t pack_bf16(float lo, float hi) { uint32_t r; asm("cvt.rn.bf16x2.f32 %0, %1, %2;" : "=r"(r) : "f"(hi), "f"(lo)); return r; }
__device__ __forceinline__ void stsm_t(uint32_t addr, uint32_t r0, uint32_t r1, uint32_t r2, uint32_t r3) {
    asm volatile("stmatrix.sync.aligned.m8n8.x4.trans.shared.b16 [%0], {%1, %2, %3, %4};" :: "r"(addr), "r"(r0), "r"(r1), "r"(r2), "r"(r3) : "memory");
}
__device__ __forceinline__ void stsm(uint32_t addr, uint32_t r0, uint32_t r1, uint32_t r2, uint32_t r3) {
    asm volatile("stmatrix.sync.aligned.m8n8.x4.shared.b16 [%0], {%1, %2, %3, %4};" :: "r"(addr), "r"(r0), "r"(r1), "r"(r2), "r"(r3) : "memory");
}
template <int OFF> __device__ __forceinline__ float4 lds_f4(uint32_t addr) {
    float4 v;
    asm volatile("ld.shared.v4.f32 {%0, %1, %2, %3}, [%4 + %5];" : "=f"(v.x), "=f"(v.y), "=f"(v.z), "=f"(v.w) : "r"(addr), "n"(OFF) : "memory");
    return v;
}
__device__ __forceinline__ float lds_f(uint32_t addr) { float v; asm volatile("ld.shared.f32 %0, [%1];" : "=f"(v) : "r"(addr) : "memory"); return v; }
__device__ __forceinline__ void sts_f(uint32_t addr, float v) { asm volatile("st.shared.f32 [%0], %1;" :: "r"(addr), "f"(v) : "memory"); }

constexpr uint32_t HI_128 = (1u << 30) | 64u;
constexpr uint32_t HI_64 = (2u << 30) | 32u;
__device__ __forceinline__ uint32_t uniform(uint32_t v) { return __shfl_sync(0xffffffffu, v, 0); }
__device__ __forceinline__ bool elect_one() {
    uint32_t r;
    asm volatile("{\n.reg .pred p;\nelect.sync _|p, 0xffffffff;\nselp.u32 %0, 1, 0, p;\n}" : "=r"(r));
    return r != 0;
}

template <int TA, uint32_t HA = HI_128, uint32_t HB = HI_128>
__device__ __forceinline__ void mma(float (&d)[48], uint32_t a, uint32_t b, int acc) {
    asm volatile("{\n.reg .pred p;\n.reg .b64 da, db;\nsetp.ne.b32 p, %50, 0;\n"
                 "mov.b64 da, {%48, %52};\nmov.b64 db, {%49, %53};\n"
                 "wgmma.mma_async.sync.aligned.m64n96k16.f32.bf16.bf16 "
                 "{%0, %1, %2, %3, %4, %5, %6, %7, %8, %9, %10, %11, %12, %13, %14, %15, %16, %17, %18, %19, %20, %21, %22, %23, "
                 "%24, %25, %26, %27, %28, %29, %30, %31, %32, %33, %34, %35, %36, %37, %38, %39, %40, %41, %42, %43, %44, %45, %46, %47}, "
                 "da, db, p, 1, 1, %51, 0;\n}"
                 : "+f"(d[0]), "+f"(d[1]), "+f"(d[2]), "+f"(d[3]), "+f"(d[4]), "+f"(d[5]), "+f"(d[6]), "+f"(d[7]),
                   "+f"(d[8]), "+f"(d[9]), "+f"(d[10]), "+f"(d[11]), "+f"(d[12]), "+f"(d[13]), "+f"(d[14]), "+f"(d[15]),
                   "+f"(d[16]), "+f"(d[17]), "+f"(d[18]), "+f"(d[19]), "+f"(d[20]), "+f"(d[21]), "+f"(d[22]), "+f"(d[23]),
                   "+f"(d[24]), "+f"(d[25]), "+f"(d[26]), "+f"(d[27]), "+f"(d[28]), "+f"(d[29]), "+f"(d[30]), "+f"(d[31]),
                   "+f"(d[32]), "+f"(d[33]), "+f"(d[34]), "+f"(d[35]), "+f"(d[36]), "+f"(d[37]), "+f"(d[38]), "+f"(d[39]),
                   "+f"(d[40]), "+f"(d[41]), "+f"(d[42]), "+f"(d[43]), "+f"(d[44]), "+f"(d[45]), "+f"(d[46]), "+f"(d[47])
                 : "r"(a), "r"(b), "r"(acc), "n"(TA), "n"(HA), "n"(HB));
}

__device__ __forceinline__ void mma32(float (&d)[16], uint32_t a, uint32_t b, int acc) {
    asm volatile("{\n.reg .pred p;\n.reg .b64 da, db;\nsetp.ne.b32 p, %18, 0;\n"
                 "mov.b64 da, {%16, %19};\nmov.b64 db, {%17, %20};\n"
                 "wgmma.mma_async.sync.aligned.m64n32k16.f32.bf16.bf16 "
                 "{%0, %1, %2, %3, %4, %5, %6, %7, %8, %9, %10, %11, %12, %13, %14, %15}, da, db, p, 1, 1, 0, 1;\n}"
                 : "+f"(d[0]), "+f"(d[1]), "+f"(d[2]), "+f"(d[3]), "+f"(d[4]), "+f"(d[5]), "+f"(d[6]), "+f"(d[7]),
                   "+f"(d[8]), "+f"(d[9]), "+f"(d[10]), "+f"(d[11]), "+f"(d[12]), "+f"(d[13]), "+f"(d[14]), "+f"(d[15])
                 : "r"(a), "r"(b), "r"(acc), "n"(HI_128), "n"(HI_64));
}

__device__ __forceinline__ void store_tile_t(const float (&d)[48], uint32_t addr, int step) {
#pragma unroll
    for (int n = 0; n < 6; n++)
        stsm_t(addr + n * step, pack_bf16(d[8 * n], d[8 * n + 1]), pack_bf16(d[8 * n + 2], d[8 * n + 3]),
               pack_bf16(d[8 * n + 4], d[8 * n + 5]), pack_bf16(d[8 * n + 6], d[8 * n + 7]));
}

template <bool MAX>
__device__ __forceinline__ void column_reduce(float (&v)[24], uint32_t red_addr, int lane) {
    const bool b4 = lane & 16, b3 = lane & 8, b2 = lane & 4;
    float a[12], b[6], c[3];
#pragma unroll
    for (int i = 0; i < 12; i++) {
        float keep = b4 ? v[12 + i] : v[i], send = b4 ? v[i] : v[12 + i];
        float o = __shfl_xor_sync(0xffffffffu, send, 16);
        a[i] = MAX ? fmaxf(keep, o) : keep + o;
    }
#pragma unroll
    for (int i = 0; i < 6; i++) {
        float keep = b3 ? a[6 + i] : a[i], send = b3 ? a[i] : a[6 + i];
        float o = __shfl_xor_sync(0xffffffffu, send, 8);
        b[i] = MAX ? fmaxf(keep, o) : keep + o;
    }
#pragma unroll
    for (int i = 0; i < 3; i++) {
        float keep = b2 ? b[3 + i] : b[i], send = b2 ? b[i] : b[3 + i];
        float o = __shfl_xor_sync(0xffffffffu, send, 4);
        c[i] = MAX ? fmaxf(keep, o) : keep + o;
    }
    const uint32_t a0 = red_addr + 4 * (24 * (lane & 3) + (b4 ? 12 : 0) + (b3 ? 6 : 0) + (b2 ? 3 : 0));
#pragma unroll
    for (int i = 0; i < 3; i++) sts_f(a0 + 4 * i, c[i]);
}

template <int N, class F> __device__ __forceinline__ void static_for(F&& f) {
    if constexpr (N > 0) { static_for<N - 1>(f); f(std::integral_constant<int, N - 1>{}); }
}

__device__ __forceinline__ uint32_t store_offset() {
    uint32_t t;
    asm volatile("mov.u32 %0, %%tid.x;" : "=r"(t));
    const uint32_t lane = t & 31, warp = (t >> 5) & 3;
    return ((lane >> 4) * 8 + (lane & 7)) * 128 + (((2 * warp + ((lane >> 3) & 1)) ^ (lane & 7)) << 4);
}

struct Ring { int slot; uint32_t phase; };
template <int N> __device__ __forceinline__ void ring_next(Ring& r) { if (++r.slot == N) { r.slot = 0; r.phase ^= 1; } }

__device__ __forceinline__ void slow_unit(uint32_t sb, const __nv_bfloat16* __restrict__ kg, const __nv_bfloat16* __restrict__ vg, int tid) {
    if (tid >= SQ) return;
    const uint32_t qrow = sb + OFF_Q + tid * 128, orow = sb + OFF_P + tid * 128;
    auto score = [&](int key) {
        float s = 0.f;
#pragma unroll 1
        for (int c = 0; c < 16; c++) {
            uint4 qv, kv = *reinterpret_cast<const uint4*>(kg + key * DH + c * 8);
            asm volatile("ld.shared.v4.u32 {%0, %1, %2, %3}, [%4];" : "=r"(qv.x), "=r"(qv.y), "=r"(qv.z), "=r"(qv.w)
                         : "r"(qrow + (c >> 3) * TILE + (((c & 7) ^ (tid & 7)) << 4)));
            const uint32_t qa[4] = {qv.x, qv.y, qv.z, qv.w}, ka[4] = {kv.x, kv.y, kv.z, kv.w};
#pragma unroll
            for (int u = 0; u < 4; u++) {
                s = fmaf(__uint_as_float(qa[u] << 16), __uint_as_float(ka[u] << 16), s);
                s = fmaf(__uint_as_float(qa[u] & 0xffff0000u), __uint_as_float(ka[u] & 0xffff0000u), s);
            }
        }
        return s;
    };
    float m = -INFINITY;
#pragma unroll 1
    for (int key = 0; key < SK; key++) m = fmaxf(m, score(key));
#pragma unroll 1
    for (int c0 = 0; c0 < 16; c0 += 4) {
        float acc[32], l = 0.f;
#pragma unroll
        for (int u = 0; u < 32; u++) acc[u] = 0.f;
#pragma unroll 1
        for (int key = 0; key < SK; key++) {
            const float p = exp2f(score(key) - m);
            l += p;
#pragma unroll
            for (int c = 0; c < 4; c++) {
                const uint4 vv = *reinterpret_cast<const uint4*>(vg + key * DH + (c0 + c) * 8);
                const uint32_t va[4] = {vv.x, vv.y, vv.z, vv.w};
#pragma unroll
                for (int u = 0; u < 4; u++) {
                    acc[8 * c + 2 * u] = fmaf(p, __uint_as_float(va[u] << 16), acc[8 * c + 2 * u]);
                    acc[8 * c + 2 * u + 1] = fmaf(p, __uint_as_float(va[u] & 0xffff0000u), acc[8 * c + 2 * u + 1]);
                }
            }
        }
        const float inv = 1.f / l;
#pragma unroll
        for (int c = 0; c < 4; c++) {
            const int cc = c0 + c;
            asm volatile("st.shared.v4.u32 [%0], {%1, %2, %3, %4};" :: "r"(orow + (cc >> 3) * TILE + (((cc & 7) ^ (tid & 7)) << 4)),
                         "r"(pack_bf16(acc[8 * c] * inv, acc[8 * c + 1] * inv)), "r"(pack_bf16(acc[8 * c + 2] * inv, acc[8 * c + 3] * inv)),
                         "r"(pack_bf16(acc[8 * c + 4] * inv, acc[8 * c + 5] * inv)), "r"(pack_bf16(acc[8 * c + 6] * inv, acc[8 * c + 7] * inv)) : "memory");
        }
    }
}

__global__ void __cluster_dims__(2, 1, 1) __launch_bounds__(512, 1)
fused_attn_kernel(const __grid_constant__ CUtensorMap map_x, const __grid_constant__ CUtensorMap map_k,
                  const __grid_constant__ CUtensorMap map_v, const __grid_constant__ CUtensorMap map_wq,
                  const __grid_constant__ CUtensorMap map_wo, const __grid_constant__ CUtensorMap map_wo32,
                  const __grid_constant__ CUtensorMap map_out, const __grid_constant__ CUtensorMap map_out32,
                  const __nv_bfloat16* __restrict__ x, const __nv_bfloat16* __restrict__ kc, const __nv_bfloat16* __restrict__ vc,
                  const __nv_bfloat16* __restrict__ wq, const __nv_bfloat16* __restrict__ wo) {
    extern __shared__ __align__(1024) uint8_t smem_raw[];
    const int tid = threadIdx.x & 127, wg = uniform(threadIdx.x >> 7), warp = uniform(tid >> 5), lane = tid & 31;
    const int b = blockIdx.x % NB, g = blockIdx.x / NB;
    const uint32_t sb = SB0 + ((blockIdx.x & 1) << 24);

    if (threadIdx.x == 0) {
        if (smem_u32(smem_raw) != sb) __trap();
        for (int i = 0; i < KV_SLOTS; i++) { mbar_init(sb + BAR_KVF + 8 * i, 1); mbar_init(sb + BAR_KVE + 8 * i, 4); }
        for (int i = 0; i < PR_SLOTS; i++) { mbar_init(sb + BAR_PQF + 8 * i, 1); mbar_init(sb + BAR_POF + 8 * i, 1); mbar_init(sb + BAR_PE + 8 * i, 8); }
        mbar_init(sb + BAR_QF, 4); mbar_init(sb + BAR_QE, 4); mbar_init(sb + BAR_OF, 4); mbar_init(sb + BAR_OE, 1);
        asm volatile("fence.mbarrier_init.release.cluster;" ::: "memory");
    }
    if (threadIdx.x >= 128 && threadIdx.x < 128 + 104) {
        const int r = threadIdx.x - 128;
        asm volatile("st.shared.v4.u32 [%0], {%1, %2, %2, %2};" :: "r"(sb + OFF_REFB + 16 * r), "r"(r < 96 ? 0u : 0x3f80u), "r"(0u) : "memory");
    }
    if (threadIdx.x >= 256 && threadIdx.x < 256 + 8) asm volatile("st.shared.u32 [%0], %1;" :: "r"(sb + OFF_CNT + 4 * (threadIdx.x - 256)), "r"(0u) : "memory");
    fence_async_smem();
    __syncthreads();
    asm volatile("barrier.cluster.arrive.release.aligned;" ::: "memory");

    if (wg == 0) {
        asm volatile("setmaxnreg.inc.sync.aligned.u32 200;");
        cluster_wait();
        const uint32_t st_off = store_offset();
        float o0[48], o1[48], s[48], l[24];
        Ring kv{0, 0};

        auto issue_s = [&](int with_ref) {
            const uint32_t ka = (SB0 + OFF_KV + kv.slot * KV_BYTES) >> 4;
            wg_fence();
            if (with_ref) mma<0, 0, 8>(s, (SB0 + OFF_ONES) >> 4, (SB0 + OFF_REFB) >> 4, 0);
#pragma unroll
            for (int k = 0; k < 8; k++)
                mma<0>(s, ka + (k >> 2) * 512 + (k & 3) * 2, ((SB0 + OFF_Q + (k >> 2) * TILE) >> 4) + (k & 3) * 2, k > 0 ? 1 : with_ref);
            wg_commit();
        };
        auto issue_pv = [&](uint32_t pbuf, int acc) {
            const uint32_t va = (SB0 + OFF_KV + kv.slot * KV_BYTES) >> 4, pa = (pbuf & 0xffffff) >> 4;
            wg_fence();
#pragma unroll
            for (int k = 0; k < 4; k++) {
                mma<1>(o0, va + k * 128, pa + k * 2, k > 0 ? 1 : acc);
                mma<1>(o1, va + 512 + k * 128, pa + k * 2, k > 0 ? 1 : acc);
            }
            wg_commit();
        };
        auto softmax_store = [&](uint32_t pbuf) {
#pragma unroll
            for (int n = 0; n < 6; n++) {
#pragma unroll
                for (int j = 8 * n; j < 8 * n + 8; j++) s[j] = ex2v(s[j]);
                stsm_t(pbuf + st_off + n * 2048, pack_bf16(s[8 * n], s[8 * n + 1]), pack_bf16(s[8 * n + 2], s[8 * n + 3]),
                       pack_bf16(s[8 * n + 4], s[8 * n + 5]), pack_bf16(s[8 * n + 6], s[8 * n + 7]));
            }
#pragma unroll
            for (int j = 0; j < 12; j++) { l[2 * j] += s[4 * j] + s[4 * j + 2]; l[2 * j + 1] += s[4 * j + 1] + s[4 * j + 3]; }
        };
        auto block = [&](uint32_t pbuf, int first, int vprev) -> int {
            Ring vr = kv;
            ring_next<KV_SLOTS>(vr);
            const bool k_ok = mbar_test(sb + BAR_KVF + 8 * kv.slot, kv.phase), v_ok = mbar_test(sb + BAR_KVF + 8 * vr.slot, vr.phase);
            softmax_store(pbuf);
            if (!first) { wg_wait<0>(); warp_arrive(sb + BAR_KVE + 8 * vprev); }
            fence_async_smem();
            bar_sync(1);
            if (!k_ok) mbar_wait(sb + BAR_KVF + 8 * kv.slot, kv.phase);
            issue_s(1);
            const int kslot = kv.slot;
            kv = vr;
            if (!v_ok) mbar_wait(sb + BAR_KVF + 8 * kv.slot, kv.phase);
            issue_pv(pbuf, !first);
            ring_next<KV_SLOTS>(kv);
            wg_wait<1>();
            warp_arrive(sb + BAR_KVE + 8 * kslot);
            return vr.slot;
        };

#pragma unroll 1
        for (int i = 0; i < NSTEP; i++) {
            kv.slot = uniform(kv.slot);
            kv.phase = uniform(kv.phase);
            mbar_wait(sb + BAR_KVF + 8 * kv.slot, kv.phase);
            mbar_wait(sb + BAR_QF, i & 1);
            TL(0, 4 * i);
            TC(0, 40 + i);
            issue_s(0);
            mbar_wait(sb + BAR_OE, (i & 1) ^ 1);
            wg_wait<0>();
            warp_arrive(sb + BAR_KVE + 8 * kv.slot);
            ring_next<KV_SLOTS>(kv);
#pragma unroll
            for (int j = 0; j < 12; j++) { l[2 * j] = fmaxf(s[4 * j], s[4 * j + 2]); l[2 * j + 1] = fmaxf(s[4 * j + 1], s[4 * j + 3]); }
            column_reduce<true>(l, sb + OFF_RED + warp * 384, lane);
            bar_sync(1);
            bool bad = false;
            if (tid < SQ) {
                const uint32_t ra = sb + OFF_RED + 4 * tid;
                const float m = fmaxf(fmaxf(lds_f(ra), lds_f(ra + 384)), fmaxf(lds_f(ra + 768), lds_f(ra + 1152)));
                bad = !(fabsf(m) <= REF_LIMIT);
                const int t = tid / 24, u = tid % 24;
                asm volatile("st.shared.u32 [%0], %1;" :: "r"(sb + OFF_REFB + 16 * (8 * (u >> 1) + 2 * t + (u & 1))), "r"(pack_bf16(bad ? 0.f : -0.5f * m, 0.f)) : "memory");
            }
#pragma unroll
            for (int j = 0; j < 24; j++) l[j] = 0.f;
            fence_async_smem();
            bar_sync(1);
            wg_fence();
            mma<0, 0, 8>(s, (SB0 + OFF_ONES) >> 4, (SB0 + OFF_REFB) >> 4, 1);
            wg_commit();
            wg_wait<0>();
            TL(0, 4 * i + 1);
            int vslot = block(sb + OFF_P, 1, 0);
#pragma unroll 1
            for (int j = 1; j < 7; j++) {
                if (i == 5) TC(0, 64 + j * 10);
                vslot = block(sb + OFF_P + (j & 1) * TILE, 0, vslot);
                if (i == 5) TC(0, 64 + j * 10 + 9);
            }
            const bool v_ok = mbar_test(sb + BAR_KVF + 8 * kv.slot, kv.phase);
            softmax_store(sb + OFF_P + TILE);
            wg_wait<0>();
            warp_arrive(sb + BAR_KVE + 8 * vslot);
#pragma unroll
            for (int j = 0; j < 24; j++) bad |= !(l[j] <= SUM_LIMIT);
            fence_async_smem();
            bad = bar_or(2, bad);
            if (!bad) warp_arrive(sb + BAR_QE);
            if (!v_ok) mbar_wait(sb + BAR_KVF + 8 * kv.slot, kv.phase);
            issue_pv(sb + OFF_P + TILE, 1);
            TL(0, 4 * i + 2);
            column_reduce<false>(l, sb + OFF_RED + warp * 384, lane);
            bar_sync(1);
            if (tid < SQ) {
                const uint32_t ra = sb + OFF_RED + 4 * tid;
                sts_f(sb + OFF_INV + 4 * tid, 1.f / ((lds_f(ra) + lds_f(ra + 384)) + (lds_f(ra + 768) + lds_f(ra + 1152))));
            }
            wg_wait<0>();
            warp_arrive(sb + BAR_KVE + 8 * kv.slot);
            ring_next<KV_SLOTS>(kv);
            bar_sync(1);
            if (!bad) {
                const uint32_t col_off = sb + 96 * (lane & 3);
                static_for<6>([&](auto nc) {
                    constexpr int n = decltype(nc)::value;
                    const float4 r = lds_f4<OFF_INV + 16 * n>(col_off);
                    o0[8 * n] *= r.x; o0[8 * n + 1] *= r.y; o0[8 * n + 2] *= r.x; o0[8 * n + 3] *= r.y;
                    o0[8 * n + 4] *= r.z; o0[8 * n + 5] *= r.w; o0[8 * n + 6] *= r.z; o0[8 * n + 7] *= r.w;
                    o1[8 * n] *= r.x; o1[8 * n + 1] *= r.y; o1[8 * n + 2] *= r.x; o1[8 * n + 3] *= r.y;
                    o1[8 * n + 4] *= r.z; o1[8 * n + 5] *= r.w; o1[8 * n + 6] *= r.z; o1[8 * n + 7] *= r.w;
                });
                store_tile_t(o0, sb + OFF_P + st_off, 2048);
                store_tile_t(o1, sb + OFF_P + TILE + st_off, 2048);
            } else {
                const size_t u = (size_t)(b * NH + g * NSTEP + i) * SK * DH;
                slow_unit(sb, kc + u, vc + u, tid);
                warp_arrive(sb + BAR_QE);
            }
            fence_async_smem();
            warp_arrive(sb + BAR_OF);
            TL(0, 4 * i + 3);
            TC(0, 50 + i);
        }
    } else if (wg == 1) {
        asm volatile("setmaxnreg.dec.sync.aligned.u32 128;");
        cluster_wait();
        const uint32_t st_off = store_offset();
        float q0[48], q1[48];
        int slot = 0;
        uint32_t phases = 0;
#pragma unroll 1
        for (int i = 0; i < NSTEP; i++) {
            TL(1, 4 * i);
            int prev = -1;
#pragma unroll 1
            for (int st = 0; st < DM / 64; st++) {
                const uint32_t ba = (SB0 + OFF_PR + slot * PR_BYTES) >> 4;
                if (!mbar_test(sb + BAR_PQF + 8 * slot, (phases >> slot) & 1)) {
                    wg_wait<0>();
                    if (prev >= 0) warp_arrive_pair(sb + BAR_PE + 8 * prev);
                    prev = -1;
                    mbar_wait(sb + BAR_PQF + 8 * slot, (phases >> slot) & 1);
                }
                if (i == 6) TC(1, 64 + st * 2);
                if (i == 0) TL(1, 100 + st);
                phases ^= 1u << slot;
                wg_fence();
#pragma unroll
                for (int k = 0; k < 4; k++) {
                    mma<1>(q0, ba + TILE / 16 + k * 128, ba + k * 2, k > 0 ? 1 : st);
                    mma<1>(q1, ba + TILE / 16 + 512 + k * 128, ba + k * 2, k > 0 ? 1 : st);
                    if (k == 1) {
                        wg_commit();
                        wg_wait<1>();
                        if (prev >= 0) warp_arrive_pair(sb + BAR_PE + 8 * prev);
                    }
                }
                wg_commit();
                prev = slot;
                if (++slot == PR_SLOTS) slot = 0;
            }
            wg_wait<0>();
            warp_arrive_pair(sb + BAR_PE + 8 * prev);
            if (i >= 2) slot = (slot + 8) % PR_SLOTS;
            TL(1, 4 * i + 1);
#pragma unroll
            for (int j = 0; j < 48; j++) { q0[j] *= SM_SCALE_LOG2; q1[j] *= SM_SCALE_LOG2; }
            mbar_wait(sb + BAR_QE, (i & 1) ^ 1);
            store_tile_t(q0, sb + OFF_Q + st_off, 2048);
            store_tile_t(q1, sb + OFF_Q + TILE + st_off, 2048);
            fence_async_smem();
            warp_arrive(sb + BAR_QF);
            TL(1, 4 * i + 2);
        }
    } else if (wg == 2) {
        asm volatile("setmaxnreg.inc.sync.aligned.u32 160;");
        cluster_wait();
        float c0[48], c1[48], c2[16], c3[16];
        int slot = (3 * (DM / 64)) % PR_SLOTS;
        uint32_t phases = 0;
#pragma unroll 1
        for (int i = 0; i < NSTEP; i++) {
            int prev = -1;
#pragma unroll 1
            for (int st = 0; st < 8; st++) {
                const uint32_t ba = (SB0 + OFF_PR + slot * PR_BYTES) >> 4;
                if (!mbar_test(sb + BAR_POF + 8 * slot, (phases >> slot) & 1)) {
                    wg_wait<0>();
                    if (prev >= 0) warp_arrive_pair(sb + BAR_PE + 8 * prev);
                    prev = -1;
                    mbar_wait(sb + BAR_POF + 8 * slot, (phases >> slot) & 1);
                }
                if (st == 0) TL(2, 4 * i);
                if (i == 4) TC(2, 64 + st * 2);
                phases ^= 1u << slot;
                const int acc = i | st;
                wg_fence();
#pragma unroll
                for (int k = 0; k < 4; k++) {
                    mma<1>(c0, ba + TILE / 16 + k * 128, ba + k * 2, k > 0 ? 1 : acc);
                    mma<1>(c1, ba + TILE / 16 + 512 + k * 128, ba + k * 2, k > 0 ? 1 : acc);
                    mma32(c2, ba + k * 2, ba + TILE / 16 + 1024 + k * 64, k > 0 ? 1 : acc);
                    mma32(c3, ba + 512 + k * 2, ba + TILE / 16 + 1024 + k * 64, k > 0 ? 1 : acc);
                    if (k == 0) {
                        wg_commit();
                        wg_wait<1>();
                        if (prev >= 0) warp_arrive_pair(sb + BAR_PE + 8 * prev);
                    }
                }
                wg_commit();
                prev = (i == NSTEP - 1 && st >= 8 - PR_SLOTS) ? -1 : slot;
                if (++slot == PR_SLOTS) slot = 0;
            }
            wg_wait<0>();
            if (prev >= 0) warp_arrive_pair(sb + BAR_PE + 8 * prev);
            if (i < NSTEP - 3) slot = (slot + DM / 64) % PR_SLOTS;
            TL(2, 4 * i + 1);
        }
        const uint32_t st_off = store_offset();
        store_tile_t(c0, sb + OFF_KV + st_off, 2048);
        store_tile_t(c1, sb + OFF_KV + TILE + st_off, 2048);
        {
            const int row = 16 * warp + (lane & 15);
            const uint32_t ra = sb + OFF_KV + 2 * TILE + row * 64;
#pragma unroll
            for (int n = 0; n < 2; n++) {
                const uint32_t co = ((2 * n + (lane >> 4)) ^ ((row >> 1) & 3)) << 4;
                stsm(ra + co, pack_bf16(c2[8 * n], c2[8 * n + 1]), pack_bf16(c2[8 * n + 2], c2[8 * n + 3]),
                     pack_bf16(c2[8 * n + 4], c2[8 * n + 5]), pack_bf16(c2[8 * n + 6], c2[8 * n + 7]));
                if (warp < 2)
                    stsm(ra + 4096 + co, pack_bf16(c3[8 * n], c3[8 * n + 1]), pack_bf16(c3[8 * n + 2], c3[8 * n + 3]),
                         pack_bf16(c3[8 * n + 4], c3[8 * n + 5]), pack_bf16(c3[8 * n + 6], c3[8 * n + 7]));
            }
        }
        fence_async_smem();
        bar_sync(3);
        if (tid == 0) {
            tma_store_2d(&map_out, g * OCOLS, b * SQ, sb + OFF_KV);
            tma_store_2d(&map_out, g * OCOLS + 64, b * SQ, sb + OFF_KV + TILE);
            tma_store_2d(&map_out32, g * OCOLS + 128, b * SQ, sb + OFF_KV + 2 * TILE);
            asm volatile("cp.async.bulk.commit_group;" ::: "memory");
            asm volatile("cp.async.bulk.wait_group 0;" ::: "memory");
        }
        TL(2, 40);
    } else {
        asm volatile("setmaxnreg.dec.sync.aligned.u32 24;");
        if (warp != 1) cluster_wait();
        if (warp == 0) {
            asm volatile("bar.sync 4, 64;" ::: "memory");
            if (elect_one()) {
                uint64_t pol;
                asm volatile("createpolicy.fractional.L2::evict_first.b64 %0, 1.0;" : "=l"(pol));
                Ring w{0, 1}, t{0, 0};
                const int row0 = (b * NH + g * NSTEP) * SK;
#pragma unroll 1
                for (int c = 0; c < NSTEP * 16; c++) {
                    const int r = c & 15;
                    const bool is_v = (r == 15) || (r > 0 && !(r & 1));
                    const int blk = is_v ? (r == 15 ? 7 : (r >> 1) - 1) : ((r + 1) >> 1);
                    if (c >= KV_INFLIGHT) { mbar_wait(sb + BAR_KVF + 8 * t.slot, t.phase); ring_next<KV_SLOTS>(t); }
                    if (c < 8) TL(3, 200 + c);
                    if (KVPF > 0 && c == KV_SLOTS) {
                        l2_prefetch(kc + (size_t)(row0 + 3 * 64) * DH, ((KVPF + 1) / 2) * KV_BYTES);
                        l2_prefetch(vc + (size_t)(row0 + 2 * 64) * DH, (KVPF / 2) * KV_BYTES);
                    }
                    mbar_wait(sb + BAR_KVE + 8 * w.slot, w.phase);
                    mbar_expect_tx(sb + BAR_KVF + 8 * w.slot, KV_BYTES);
                    tma_3d_hint(sb + OFF_KV + w.slot * KV_BYTES, is_v ? &map_v : &map_k, 0, row0 + (c >> 4) * SK + blk * 64, 0, sb + BAR_KVF + 8 * w.slot, pol);
                    ring_next<KV_SLOTS>(w);
                }
            }
        } else if (warp == 1) {
            const int rank = b & 1;
            if (elect_one()) {
                l2_prefetch(x + (size_t)(b * SQ + g * (SQ / NG)) * DM, (SQ / NG) * DM * 2);
                if (b < 20) tma_prefetch_2d(&map_wq, g * NSTEP * DH + rank * 64, (b >> 1) * 64);
            }
            cluster_wait();
            unsigned base = 0;
            Ring w{0, 1};
            int pub = -1;
#pragma unroll 1
            for (int ph = 0; ph < NSTEP + 2; ph++) {
                if (ph < NSTEP) {
#pragma unroll 1
                    for (int st = 0; st < DM / 64; st++) {
                        mbar_wait(sb + BAR_PE + 8 * w.slot, w.phase);
                        --pub;
                        if (elect_one()) {
                            if (ph == 6) TC(3, 64 + st * 4 + 1);
                            const uint32_t dst = sb + OFF_PR + w.slot * PR_BYTES, bar = sb + BAR_PQF + 8 * w.slot;
                            mbar_expect_tx(bar, TILE + 16384);
                            tma_2d_mc(dst + TILE + rank * 8192, &map_wq, (g * NSTEP + ph) * DH + rank * 64, st * 64, bar);
                            tma_2d(dst, &map_x, st * 64, b * SQ, bar);
                            if (pub == 0) flag_set_relaxed(&g_cons[blockIdx.x * 32], base + ph - 2);
                            if (st == PR_SLOTS - 1) {
                                if (ph + 1 < NSTEP && b < 20) tma_prefetch_2d(&map_wq, (g * NSTEP + ph + 1) * DH + rank * 64, (b >> 1) * 64);
                                if (ph >= 1) l2_prefetch(wo + (size_t)((g * NSTEP + ph - 1) * DH + 4 * b) * DM, 4 * DM * 2);
                                if (ph == NSTEP - 1) l2_prefetch(wo + (size_t)((g * NSTEP + ph) * DH + 4 * b) * DM, 4 * DM * 2);
                            }
                            if (ph == 6) TC(3, 64 + st * 4 + 2);
                            if (ph == 0) TL(3, 210 + st);
                        }
                        if (ph == 0 && st == PR_SLOTS - 1) asm volatile("bar.arrive 4, 64;" ::: "memory");
                        ring_next<PR_SLOTS>(w);
                    }
                    if (ph == 0) base = g_prog[blockIdx.x * 32];
                }
                if (ph >= 2) {
#pragma unroll 1
                    for (int st = 0; st < 8; st++) {
                        mbar_wait(sb + BAR_PE + 8 * w.slot, w.phase);
                        --pub;
                        if (elect_one()) {
                            if (ph == 6) TC(3, 128 + st * 4 + 1);
                            const uint32_t dst = sb + OFF_PR + w.slot * PR_BYTES, bar = sb + BAR_POF + 8 * w.slot;
                            const int gs = (g + (st >> 1)) & (NG - 1);
                            const int krow = (gs * NSTEP + ph - 2) * DH + (st & 1) * 64;
                            mbar_expect_tx(bar, PR_BYTES);
                            tma_2d_mc(dst + TILE + rank * 8192, &map_wo, g * OCOLS + rank * 64, krow, bar);
                            tma_2d_mc(dst + TILE + 16384 + rank * 2048, &map_wo32, g * OCOLS + 128, krow + rank * 32, bar);
                            if (pub == 0) flag_set_relaxed(&g_cons[blockIdx.x * 32], base + ph - 2);
                            if (ph == 6) TC(3, 128 + st * 4 + 2);
                            if (!(st & 1)) cnt_wait(sb + OFF_CNT + 4 * gs, ph - 1);
                            bulk_load(dst, g_oscr + (size_t)(((ph & 1) * NCTA + gs * NB + b) * 2 + (st & 1)) * TILE, TILE, bar);
                            if (ph == 6) TC(3, 128 + st * 4 + 3);
                        }
                        ring_next<PR_SLOTS>(w);
                    }
                    pub = PR_SLOTS;
                }
            }
        } else if (warp == 2) {
            if (elect_one()) {
                const unsigned base = g_prog[blockIdx.x * 32];
#pragma unroll 1
                for (int i = 0; i < NSTEP; i++) {
                    if (i >= 2)
                        for (int gs = 0; gs < NG; gs++) cnt_wait(sb + OFF_CNT + 16 + 4 * gs, i - 1);
                    mbar_wait(sb + BAR_OF, i & 1);
                    if (i == 5) TC(3, 32);
                    bulk_store(g_oscr + (size_t)((i & 1) * NCTA + blockIdx.x) * 2 * TILE, sb + OFF_P, 2 * TILE);
                    asm volatile("cp.async.bulk.commit_group;" ::: "memory");
                    asm volatile("cp.async.bulk.wait_group.read 0;" ::: "memory");
                    if (i == 5) TC(3, 33);
                    mbar_arrive(sb + BAR_OE);
                    asm volatile("cp.async.bulk.wait_group 0;" ::: "memory");
                    if (i == 5) TC(3, 34);
                    flag_set(&g_prog[blockIdx.x * 32], base + i + 1);
                    if (i == 5) TC(3, 35);
                    TL(3, i);
                }
            }
        } else if (lane < 8) {
            const unsigned base = g_prog[blockIdx.x * 32];
            const unsigned* p = (lane < 4 ? g_prog : g_cons) + ((lane & 3) * NB + b) * 32;
            const int last = lane < 4 ? NSTEP : NSTEP - 2;
            int seen = 0;
            for (unsigned c = 0; seen < last; c++) {
                unsigned v;
                asm volatile("ld.acquire.gpu.global.u32 %0, [%1];" : "=r"(v) : "l"(p) : "memory");
                const int d = (int)(v - base);
                if (d > seen) { seen = d; asm volatile("st.release.cta.shared.u32 [%0], %1;" :: "r"(sb + OFF_CNT + 4 * lane), "r"(d) : "memory"); }
                if (c > 0x1000000u) __trap();
            }
        }
    }
}

typedef CUresult (*EncodeFn)(CUtensorMap*, CUtensorMapDataType, cuuint32_t, void*, const cuuint64_t*, const cuuint64_t*,
                             const cuuint32_t*, const cuuint32_t*, CUtensorMapInterleave, CUtensorMapSwizzle,
                             CUtensorMapL2promotion, CUtensorMapFloatOOBfill);

CUtensorMap make_map(EncodeFn fn, const void* base, int rank, const cuuint64_t* dims, const cuuint64_t* strides,
                     const cuuint32_t* box, CUtensorMapSwizzle sw, CUtensorMapL2promotion promo) {
    CUtensorMap m;
    const cuuint32_t es[3] = {1, 1, 1};
    fn(&m, CU_TENSOR_MAP_DATA_TYPE_BFLOAT16, rank, const_cast<void*>(base), dims, strides, box, es,
       CU_TENSOR_MAP_INTERLEAVE_NONE, sw, promo, CU_TENSOR_MAP_FLOAT_OOB_FILL_NONE);
    return m;
}

}

extern "C" void kernel_launch(void* const* d_in, const int* in_sizes, int n_in, void* d_out, int out_size) {
    const __nv_bfloat16* x = (const __nv_bfloat16*)d_in[0];
    const __nv_bfloat16* kc = (const __nv_bfloat16*)d_in[1];
    const __nv_bfloat16* vc = (const __nv_bfloat16*)d_in[2];
    const __nv_bfloat16* wq = (const __nv_bfloat16*)d_in[3];
    const __nv_bfloat16* wo = (const __nv_bfloat16*)d_in[4];

    void* p = nullptr;
    cudaDriverEntryPointQueryResult qr;
    cudaGetDriverEntryPoint("cuTensorMapEncodeTiled", &p, cudaEnableDefault, &qr);
    EncodeFn fn = (EncodeFn)p;
    cudaFuncSetAttribute(fused_attn_kernel, cudaFuncAttributeMaxDynamicSharedMemorySize, SMEM_BYTES);

    const auto S128 = CU_TENSOR_MAP_SWIZZLE_128B, S64 = CU_TENSOR_MAP_SWIZZLE_64B;
    const auto P256 = CU_TENSOR_MAP_L2_PROMOTION_L2_256B, P128 = CU_TENSOR_MAP_L2_PROMOTION_L2_128B;
    const cuuint64_t dx[2] = {DM, NB * SQ}, sx[1] = {DM * 2};
    const cuuint32_t bx[2] = {64, SQ}, bx32[2] = {32, SQ};
    const cuuint64_t dkv[3] = {64, (cuuint64_t)NB * NH * SK, 2}, skv[2] = {DH * 2, 128};
    const cuuint64_t dwq[2] = {NH * DH, DM}, swq[1] = {NH * DH * 2};
    const cuuint32_t b3[3] = {64, 64, 2};
    const cuuint64_t dwo[2] = {DM, NH * DH};
    const cuuint32_t bwo[2] = {64, 64}, bwo32[2] = {32, 32};

    fused_attn_kernel<<<NCTA, 512, SMEM_BYTES>>>(
        make_map(fn, x, 2, dx, sx, bx, S128, P128), make_map(fn, kc, 3, dkv, skv, b3, S128, P256),
        make_map(fn, vc, 3, dkv, skv, b3, S128, P256), make_map(fn, wq, 2, dwq, swq, bwo, S128, P128),
        make_map(fn, wo, 2, dwo, sx, bwo, S128, P128), make_map(fn, wo, 2, dwo, sx, bwo32, S64, P128),
        make_map(fn, d_out, 2, dx, sx, bx, S128, P128), make_map(fn, d_out, 2, dx, sx, bx32, S64, P128),
        x, kc, vc, wq, wo);
}
```

```cpp
#include <cuda_runtime.h>
#include <cuda.h>
#include <cuda_bf16.h>
#include <stdint.h>
#include <type_traits>

namespace {

constexpr int NB = 32, SQ = 96, DM = 640, NH = 32, SK = 512, DH = 128;
constexpr int NG = 4;
constexpr int NSTEP = NH / NG;
constexpr int NCTA = NB * NG;

#define KVW1 2
#define KVLO 2
#define KVRHI 96
#define KVSTAG 1
#define WAITHINT 1
#define PVSPLIT 2
#define PRI_Q false
#define PRI_LAST 0
#define PRI_FROM 8
#define PRI_ON 4
#define PRI_OFF 1
#define WPF 2
#define WPFNS 300
#define WPFAT 3
#define SINGLE 0
#define VREL 4

#define POLLNS 300
#define KVPROMO CU_TENSOR_MAP_L2_PROMOTION_L2_128B
#define KVS 5
#define NBS 3
#define NWS 5
constexpr int KV_SLOTS = KVS, KV_BYTES = 16384;
constexpr int TILE = 12288;
constexpr int B_SLOTS = NBS;
constexpr int W_SLOTS = NWS, W_BYTES = 12288;
constexpr int OFF_KV = 0;
constexpr int OFF_B = OFF_KV + KV_SLOTS * KV_BYTES;
constexpr int OFF_W = OFF_B + B_SLOTS * TILE;
constexpr int OFF_Q = OFF_W + W_SLOTS * W_BYTES;
constexpr int OFF_P = OFF_Q + 2 * TILE;
constexpr int OFF_RED = OFF_P;
constexpr int OFF_REFB = OFF_P + 2 * TILE;
constexpr int OFF_ONES = OFF_REFB + 96 * 16;
constexpr int OFF_INV = OFF_ONES + 128;
constexpr int OFF_CNT = OFF_INV + 96 * 4;
constexpr int OFF_PRI = OFF_CNT + 36;
constexpr int BAR_KVF = OFF_CNT + 40, BAR_KVE = BAR_KVF + 8 * KV_SLOTS;
constexpr int BAR_WQF = BAR_KVE + 8 * KV_SLOTS, BAR_WOF = BAR_WQF + 8 * W_SLOTS, BAR_WE = BAR_WOF + 8 * W_SLOTS;
constexpr int BAR_BQF = BAR_WE + 8 * W_SLOTS, BAR_BOF = BAR_BQF + 8 * B_SLOTS, BAR_BE = BAR_BOF + 8 * B_SLOTS;
constexpr int BAR_QF = BAR_BE + 8 * B_SLOTS, BAR_QE = BAR_QF + 8, BAR_OF = BAR_QE + 8, BAR_GO = BAR_OF + 8;
constexpr int SMEM_BYTES = BAR_GO + 8;
constexpr uint32_t SB0 = 1024;
static_assert(SMEM_BYTES <= 232448, "smem");

constexpr float SM_SCALE_LOG2 = 0.08838834764831845f * 1.4426950408889634f;
constexpr float SUM_LIMIT = 1.152921504606847e18f;
constexpr float REF_LIMIT = 4096.f;

__device__ __align__(1024) uint8_t g_oscr[2 * NCTA * 2 * TILE];
__device__ unsigned g_prog[NCTA * 32];
__device__ unsigned g_cons[NCTA * 32];
__device__ unsigned g_kvrank[34 * 32];

#define TL(role, idx)
#define TL2(idx)
#define TCD(role, idx)
#define TLD(role, idx)
#define WAITACC(expr) expr
#define TC(role, idx)

__device__ __forceinline__ uint32_t smem_u32(const void* p) { return (uint32_t)__cvta_generic_to_shared(p); }
__device__ __forceinline__ void mbar_init(uint32_t bar, uint32_t cnt) { asm volatile("mbarrier.init.shared::cta.b64 [%0], %1;" :: "r"(bar), "r"(cnt) : "memory"); }
__device__ __forceinline__ void mbar_expect_tx(uint32_t bar, uint32_t bytes) { asm volatile("mbarrier.arrive.expect_tx.shared::cta.b64 _, [%0], %1;" :: "r"(bar), "r"(bytes) : "memory"); }
__device__ __forceinline__ void mbar_arrive(uint32_t bar) { asm volatile("mbarrier.arrive.shared::cta.b64 _, [%0];" :: "r"(bar) : "memory"); }
__device__ __forceinline__ void mbar_wait(uint32_t bar, uint32_t parity) {
    asm volatile("{\n.reg .pred p;\n.reg .u32 c;\n"
                 "mbarrier.try_wait.parity.shared::cta.b64 p, [%0], %1;\n"
                 "@p bra LAB_DONE;\n"
                 "mov.u32 c, 0;\n"
                 "LAB_WAIT:\n"
                 "mbarrier.try_wait.parity.shared::cta.b64 p, [%0], %1, 0x4000;\n"
                 "@p bra LAB_DONE;\n"
                 "add.u32 c, c, 1;\nsetp.lt.u32 p, c, 0x100000;\n"
                 "@p bra LAB_WAIT;\n"
                 "trap;\n"
                 "LAB_DONE:\n}" :: "r"(bar), "r"(parity) : "memory");
}
__device__ __forceinline__ bool mbar_test(uint32_t bar, uint32_t parity) {
    uint32_t r;
    asm volatile("{\n.reg .pred p;\nmbarrier.test_wait.parity.shared::cta.b64 p, [%1], %2;\nselp.u32 %0, 1, 0, p;\n}" : "=r"(r) : "r"(bar), "r"(parity) : "memory");
    return r != 0;
}
__device__ __forceinline__ void warp_arrive(uint32_t bar) {
    __syncwarp();
    if ((threadIdx.x & 31) == 0) mbar_arrive(bar);
}
__device__ __forceinline__ void lane_arrive(uint32_t addr) {
    asm volatile("{\n.reg .pred p;\nsetp.ne.u32 p, %0, 0;\n@p mbarrier.arrive.shared::cluster.b64 _, [%0];\n}" :: "r"(addr) : "memory");
}
__device__ __forceinline__ void cluster_wait() { asm volatile("barrier.cluster.wait.acquire.aligned;" ::: "memory"); }
__device__ __forceinline__ void cnt_wait(uint32_t addr, int target) {
    for (unsigned c = 0;; c++) {
        int v;
        asm volatile("ld.acquire.cta.shared.u32 %0, [%1];" : "=r"(v) : "r"(addr) : "memory");
        if (v >= target) return;
        __nanosleep(64);
        if (c > 0x4000000u) __trap();
    }
}
__device__ __forceinline__ void flag_wait(const unsigned* p, unsigned target) {
    for (unsigned c = 0;; c++) {
        unsigned v;
        asm volatile("ld.acquire.gpu.global.u32 %0, [%1];" : "=r"(v) : "l"(p) : "memory");
        if ((int)(v - target) >= 0) return;
        if (c > 0x1000000u) __trap();
    }
}
__device__ __forceinline__ void flag_set_relaxed(unsigned* p, unsigned v) { asm volatile("st.relaxed.gpu.global.u32 [%0], %1;" :: "l"(p), "r"(v) : "memory"); }
__device__ __forceinline__ void flag_set(unsigned* p, unsigned v) { asm volatile("st.release.gpu.global.u32 [%0], %1;" :: "l"(p), "r"(v) : "memory"); }
__device__ __forceinline__ void fence_async_smem() { asm volatile("fence.proxy.async.shared::cta;" ::: "memory"); }
__device__ __forceinline__ void bar_sync(int id) { asm volatile("bar.sync %0, 128;" :: "r"(id) : "memory"); }
__device__ __forceinline__ bool bar_or(int id, bool v) {
    uint32_t r;
    asm volatile("{\n.reg .pred p, q;\nsetp.ne.u32 p, %2, 0;\nbar.red.or.pred q, %1, 128, p;\nselp.u32 %0, 1, 0, q;\n}" : "=r"(r) : "r"(id), "r"((uint32_t)v) : "memory");
    return r != 0;
}
__device__ __forceinline__ void tma_2d(uint32_t dst, const CUtensorMap* m, int c0, int c1, uint32_t bar) {
    asm volatile("cp.async.bulk.tensor.2d.shared::cluster.global.mbarrier::complete_tx::bytes [%0], [%1, {%3, %4}], [%2];"
                 :: "r"(dst), "l"((uint64_t)m), "r"(bar), "r"(c0), "r"(c1) : "memory");
}
__device__ __forceinline__ void tma_2d_mc(uint32_t dst, const CUtensorMap* m, int c0, int c1, uint32_t bar) {
    asm volatile("cp.async.bulk.tensor.2d.shared::cluster.global.mbarrier::complete_tx::bytes.multicast::cluster [%0], [%1, {%3, %4}], [%2], %5;"
                 :: "r"(dst), "l"((uint64_t)m), "r"(bar), "r"(c0), "r"(c1), "h"((uint16_t)3) : "memory");
}
__device__ __forceinline__ void tma_prefetch_2d(const CUtensorMap* m, int c0, int c1) {
    asm volatile("cp.async.bulk.prefetch.tensor.2d.L2.global [%0, {%1, %2}];" :: "l"((uint64_t)m), "r"(c0), "r"(c1) : "memory");
}
__device__ __forceinline__ void tma_3d_hint(uint32_t dst, const CUtensorMap* m, int c0, int c1, int c2, uint32_t bar, uint64_t pol) {
    asm volatile("cp.async.bulk.tensor.3d.shared::cluster.global.mbarrier::complete_tx::bytes.L2::cache_hint [%0], [%1, {%3, %4, %5}], [%2], %6;"
                 :: "r"(dst), "l"((uint64_t)m), "r"(bar), "r"(c0), "r"(c1), "r"(c2), "l"(pol) : "memory");
}
__device__ __forceinline__ void tma_store_2d(const CUtensorMap* m, int c0, int c1, uint32_t src) {
    asm volatile("cp.async.bulk.tensor.2d.global.shared::cta.bulk_group [%0, {%2, %3}], [%1];"
                 :: "l"((uint64_t)m), "r"(src), "r"(c0), "r"(c1) : "memory");
}
__device__ __forceinline__ void bulk_load(uint32_t dst, const void* src, uint32_t bytes, uint32_t bar) {
    asm volatile("cp.async.bulk.shared::cluster.global.mbarrier::complete_tx::bytes [%0], [%1], %2, [%3];"
                 :: "r"(dst), "l"((uint64_t)src), "r"(bytes), "r"(bar) : "memory");
}
__device__ __forceinline__ void l2_prefetch(const void* p, uint32_t bytes) {
    asm volatile("cp.async.bulk.prefetch.L2.global [%0], %1;" :: "l"((uint64_t)p), "r"(bytes) : "memory");
}
__device__ __forceinline__ void wg_fence() { asm volatile("wgmma.fence.sync.aligned;" ::: "memory"); }
__device__ __forceinline__ void wg_commit() { asm volatile("wgmma.commit_group.sync.aligned;" ::: "memory"); }
template <int N> __device__ __forceinline__ void wg_wait() { asm volatile("wgmma.wait_group.sync.aligned %0;" :: "n"(N) : "memory"); }
__device__ __forceinline__ float ex2v(float x) { float y; asm volatile("ex2.approx.ftz.f32 %0, %1;" : "=f"(y) : "f"(x)); return y; }
__device__ __forceinline__ uint32_t pack_bf16(float lo, float hi) { uint32_t r; asm("cvt.rn.bf16x2.f32 %0, %1, %2;" : "=r"(r) : "f"(hi), "f"(lo)); return r; }
__device__ __forceinline__ void stsm_t(uint32_t addr, uint32_t r0, uint32_t r1, uint32_t r2, uint32_t r3) {
    asm volatile("stmatrix.sync.aligned.m8n8.x4.trans.shared.b16 [%0], {%1, %2, %3, %4};" :: "r"(addr), "r"(r0), "r"(r1), "r"(r2), "r"(r3) : "memory");
}
template <int OFF> __device__ __forceinline__ float4 lds_f4(uint32_t addr) {
    float4 v;
    asm volatile("ld.shared.v4.f32 {%0, %1, %2, %3}, [%4 + %5];" : "=f"(v.x), "=f"(v.y), "=f"(v.z), "=f"(v.w) : "r"(addr), "n"(OFF) : "memory");
    return v;
}
__device__ __forceinline__ float lds_f(uint32_t addr) { float v; asm volatile("ld.shared.f32 %0, [%1];" : "=f"(v) : "r"(addr) : "memory"); return v; }
__device__ __forceinline__ void sts_f(uint32_t addr, float v) { asm volatile("st.shared.f32 [%0], %1;" :: "r"(addr), "f"(v) : "memory"); }

constexpr uint32_t HI_128 = (1u << 30) | 64u;
constexpr uint32_t HI_CORE = 8u;
constexpr uint32_t LBO_O = (1536u >> 4) << 16;
__device__ __forceinline__ uint32_t uniform(uint32_t v) { return __shfl_sync(0xffffffffu, v, 0); }
__device__ __forceinline__ bool elect_one() {
    uint32_t r;
    asm volatile("{\n.reg .pred p;\nelect.sync _|p, 0xffffffff;\nselp.u32 %0, 1, 0, p;\n}" : "=r"(r));
    return r != 0;
}

template <int TA, uint32_t HA = HI_128, uint32_t HB = HI_128, int TB = 0>
__device__ __forceinline__ void mma(float (&d)[48], uint32_t a, uint32_t b, int acc) {
    asm volatile("{\n.reg .pred p;\n.reg .b64 da, db;\nsetp.ne.b32 p, %50, 0;\n"
                 "mov.b64 da, {%48, %52};\nmov.b64 db, {%49, %53};\n"
                 "wgmma.mma_async.sync.aligned.m64n96k16.f32.bf16.bf16 "
                 "{%0, %1, %2, %3, %4, %5, %6, %7, %8, %9, %10, %11, %12, %13, %14, %15, %16, %17, %18, %19, %20, %21, %22, %23, "
                 "%24, %25, %26, %27, %28, %29, %30, %31, %32, %33, %34, %35, %36, %37, %38, %39, %40, %41, %42, %43, %44, %45, %46, %47}, "
                 "da, db, p, 1, 1, %51, %54;\n}"
                 : "+f"(d[0]), "+f"(d[1]), "+f"(d[2]), "+f"(d[3]), "+f"(d[4]), "+f"(d[5]), "+f"(d[6]), "+f"(d[7]),
                   "+f"(d[8]), "+f"(d[9]), "+f"(d[10]), "+f"(d[11]), "+f"(d[12]), "+f"(d[13]), "+f"(d[14]), "+f"(d[15]),
                   "+f"(d[16]), "+f"(d[17]), "+f"(d[18]), "+f"(d[19]), "+f"(d[20]), "+f"(d[21]), "+f"(d[22]), "+f"(d[23]),
                   "+f"(d[24]), "+f"(d[25]), "+f"(d[26]), "+f"(d[27]), "+f"(d[28]), "+f"(d[29]), "+f"(d[30]), "+f"(d[31]),
                   "+f"(d[32]), "+f"(d[33]), "+f"(d[34]), "+f"(d[35]), "+f"(d[36]), "+f"(d[37]), "+f"(d[38]), "+f"(d[39]),
                   "+f"(d[40]), "+f"(d[41]), "+f"(d[42]), "+f"(d[43]), "+f"(d[44]), "+f"(d[45]), "+f"(d[46]), "+f"(d[47])
                 : "r"(a), "r"(b), "r"(acc), "n"(TA), "n"(HA), "n"(HB), "n"(TB));
}

__device__ __forceinline__ void mma48(float (&d)[24], uint32_t a, uint32_t b, int acc) {
    asm volatile("{\n.reg .pred p;\n.reg .b64 da, db;\nsetp.ne.b32 p, %26, 0;\n"
                 "mov.b64 da, {%24, %27};\nmov.b64 db, {%25, %28};\n"
                 "wgmma.mma_async.sync.aligned.m64n48k16.f32.bf16.bf16 "
                 "{%0, %1, %2, %3, %4, %5, %6, %7, %8, %9, %10, %11, %12, %13, %14, %15, %16, %17, %18, %19, %20, %21, %22, %23}, "
                 "da, db, p, 1, 1, 1, 1;\n}"
                 : "+f"(d[0]), "+f"(d[1]), "+f"(d[2]), "+f"(d[3]), "+f"(d[4]), "+f"(d[5]), "+f"(d[6]), "+f"(d[7]),
                   "+f"(d[8]), "+f"(d[9]), "+f"(d[10]), "+f"(d[11]), "+f"(d[12]), "+f"(d[13]), "+f"(d[14]), "+f"(d[15]),
                   "+f"(d[16]), "+f"(d[17]), "+f"(d[18]), "+f"(d[19]), "+f"(d[20]), "+f"(d[21]), "+f"(d[22]), "+f"(d[23])
                 : "r"(a), "r"(b), "r"(acc), "n"(HI_128), "n"(HI_CORE));
}

__device__ __forceinline__ void store_tile_t(const float (&d)[48], uint32_t addr, int step) {
#pragma unroll
    for (int n = 0; n < 6; n++)
        stsm_t(addr + n * step, pack_bf16(d[8 * n], d[8 * n + 1]), pack_bf16(d[8 * n + 2], d[8 * n + 3]),
               pack_bf16(d[8 * n + 4], d[8 * n + 5]), pack_bf16(d[8 * n + 6], d[8 * n + 7]));
}

template <bool MAX>
__device__ __forceinline__ void column_reduce(const float (&v)[24], float (&c)[3], int lane) {
    const bool b4 = lane & 16, b3 = lane & 8, b2 = lane & 4;
    float a[12], b[6];
#pragma unroll
    for (int i = 0; i < 12; i++) {
        float keep = b4 ? v[12 + i] : v[i], send = b4 ? v[i] : v[12 + i];
        float o = __shfl_xor_sync(0xffffffffu, send, 16);
        a[i] = MAX ? fmaxf(keep, o) : keep + o;
    }
#pragma unroll
    for (int i = 0; i < 6; i++) {
        float keep = b3 ? a[6 + i] : a[i], send = b3 ? a[i] : a[6 + i];
        float o = __shfl_xor_sync(0xffffffffu, send, 8);
        b[i] = MAX ? fmaxf(keep, o) : keep + o;
    }
#pragma unroll
    for (int i = 0; i < 3; i++) {
        float keep = b2 ? b[3 + i] : b[i], send = b2 ? b[i] : b[3 + i];
        float o = __shfl_xor_sync(0xffffffffu, send, 4);
        c[i] = MAX ? fmaxf(keep, o) : keep + o;
    }
}

template <int N, class F> __device__ __forceinline__ void static_for(F&& f) {
    if constexpr (N > 0) { static_for<N - 1>(f); f(std::integral_constant<int, N - 1>{}); }
}

__device__ __forceinline__ uint32_t store_offset() {
    uint32_t t;
    asm volatile("mov.u32 %0, %%tid.x;" : "=r"(t));
    const uint32_t lane = t & 31, warp = (t >> 5) & 3;
    return ((lane >> 4) * 8 + (lane & 7)) * 128 + (((2 * warp + ((lane >> 3) & 1)) ^ (lane & 7)) << 4);
}

struct Ring { int slot; uint32_t phase; };
template <int N> __device__ __forceinline__ void ring_next(Ring& r) { if (++r.slot == N) { r.slot = 0; r.phase ^= 1; } }

__device__ __forceinline__ bool lds_pri(uint32_t sb) {
    uint32_t v;
    asm volatile("ld.volatile.shared.u32 %0, [%1];" : "=r"(v) : "r"(sb + OFF_PRI) : "memory");
    return v != 0;
}
__device__ __forceinline__ void sts_pri(uint32_t sb, bool pred, uint32_t v) {
    asm volatile("{\n.reg .pred p;\nsetp.ne.u32 p, %2, 0;\n@p st.volatile.shared.u32 [%0], %1;\n}" :: "r"(sb + OFF_PRI), "r"(v), "r"((uint32_t)pred) : "memory");
}

template <int NH32, bool YIELD, class F>
__device__ __forceinline__ void projection_pass(uint32_t sb, uint32_t wfull, uint32_t bfull, int& ws, int& bs, uint32_t& phases,
                                                int keep_from, int lane, F&& issue) {
    const uint32_t rel_w = lane < 2 ? (SB0 + BAR_WE) + (lane << 24) : 0, rel_b = lane == 2 ? sb + BAR_BE : 0;
    uint32_t rel = 0;
    bool ok = false;
    uint32_t wa = (SB0 + OFF_W + ws * W_BYTES) >> 4, ba = (SB0 + OFF_B + bs * TILE) >> 4;
    auto landed = [&](int odd) {
        bool r = mbar_test(wfull + 8 * ws, (phases >> ws) & 1);
        if (!odd) r &= mbar_test(bfull + 8 * bs, (phases >> (16 + bs)) & 1);
        if (YIELD) r &= !lds_pri(sb);
        return r;
    };
#pragma unroll 1
    for (int st = 0; st < NH32 / 2; st++) {
#pragma unroll
        for (int odd = 0; odd < 2; odd++) {
            if (!ok && !landed(odd)) {
                wg_wait<0>();
                lane_arrive(rel);
                rel = 0;
                mbar_wait(wfull + 8 * ws, (phases >> ws) & 1);
                if (!odd) mbar_wait(bfull + 8 * bs, (phases >> (16 + bs)) & 1);
                if (YIELD) for (int c = 0; c < 4096 && lds_pri(sb); c++) {}
            }
            wg_fence();
            issue(wa, ba, odd, st + odd);
            wg_commit();
            uint32_t nrel = (rel_w && 2 * st + odd < keep_from) ? rel_w + 8 * ws : 0;
            if (odd && rel_b) nrel = rel_b + 8 * bs;
            phases ^= odd ? (1u << ws) | (0x10000u << bs) : 1u << ws;
            if (++ws == W_SLOTS) ws = 0;
            if (odd && ++bs == B_SLOTS) bs = 0;
            wa = (SB0 + OFF_W + ws * W_BYTES) >> 4;
            ba = (SB0 + OFF_B + bs * TILE) >> 4;
            ok = landed(odd ^ 1);
            wg_wait<1>();
            lane_arrive(rel);
            rel = nrel;
        }
    }
    wg_wait<0>();
    lane_arrive(rel);
}

__device__ __forceinline__ void slow_unit(uint32_t sb, const __nv_bfloat16* __restrict__ kg, const __nv_bfloat16* __restrict__ vg,
                                          uint8_t* og, int tid) {
    if (tid >= SQ) return;
    const uint32_t qrow = sb + OFF_Q + tid * 128;
    auto score = [&](int key) {
        float s = 0.f;
#pragma unroll 1
        for (int c = 0; c < 16; c++) {
            uint4 qv, kv = *reinterpret_cast<const uint4*>(kg + key * DH + c * 8);
            asm volatile("ld.shared.v4.u32 {%0, %1, %2, %3}, [%4];" : "=r"(qv.x), "=r"(qv.y), "=r"(qv.z), "=r"(qv.w)
                         : "r"(qrow + (c >> 3) * TILE + (((c & 7) ^ (tid & 7)) << 4)));
            const uint32_t qa[4] = {qv.x, qv.y, qv.z, qv.w}, ka[4] = {kv.x, kv.y, kv.z, kv.w};
#pragma unroll
            for (int u = 0; u < 4; u++) {
                s = fmaf(__uint_as_float(qa[u] << 16), __uint_as_float(ka[u] << 16), s);
                s = fmaf(__uint_as_float(qa[u] & 0xffff0000u), __uint_as_float(ka[u] & 0xffff0000u), s);
            }
        }
        return s;
    };
    float m = -INFINITY;
#pragma unroll 1
    for (int key = 0; key < SK; key++) m = fmaxf(m, score(key));
#pragma unroll 1
    for (int c0 = 0; c0 < 16; c0 += 4) {
        float acc[32], l = 0.f;
#pragma unroll
        for (int u = 0; u < 32; u++) acc[u] = 0.f;
#pragma unroll 1
        for (int key = 0; key < SK; key++) {
            const float p = exp2f(score(key) - m);
            l += p;
#pragma unroll
            for (int c = 0; c < 4; c++) {
                const uint4 vv = *reinterpret_cast<const uint4*>(vg + key * DH + (c0 + c) * 8);
                const uint32_t va[4] = {vv.x, vv.y, vv.z, vv.w};
#pragma unroll
                for (int u = 0; u < 4; u++) {
                    acc[8 * c + 2 * u] = fmaf(p, __uint_as_float(va[u] << 16), acc[8 * c + 2 * u]);
                    acc[8 * c + 2 * u + 1] = fmaf(p, __uint_as_float(va[u] & 0xffff0000u), acc[8 * c + 2 * u + 1]);
                }
            }
        }
        const float inv = 1.f / l;
#pragma unroll
        for (int u = 0; u < 32; u++)
            *reinterpret_cast<__nv_bfloat16*>(og + (c0 + (u >> 3)) * 1536 + (tid >> 3) * 128 + (u & 7) * 16 + (tid & 7) * 2) = __float2bfloat16(acc[u] * inv);
    }
}

__global__ void __cluster_dims__(2, 1, 1) __launch_bounds__(512, 1)
fused_attn_kernel(const __grid_constant__ CUtensorMap map_x, const __grid_constant__ CUtensorMap map_k,
                  const __grid_constant__ CUtensorMap map_v, const __grid_constant__ CUtensorMap map_wq,
                  const __grid_constant__ CUtensorMap map_wo, const __grid_constant__ CUtensorMap map_wo16,
                  const __grid_constant__ CUtensorMap map_out, const __grid_constant__ CUtensorMap map_out48,
                  const __nv_bfloat16* __restrict__ x, const __nv_bfloat16* __restrict__ kc, const __nv_bfloat16* __restrict__ vc,
                  const __nv_bfloat16* __restrict__ wq, const __nv_bfloat16* __restrict__ wo) {
    extern __shared__ __align__(1024) uint8_t smem_raw[];
    const int tid = threadIdx.x & 127, wg = uniform(threadIdx.x >> 7), warp = uniform(tid >> 5), lane = tid & 31;
    const int b = blockIdx.x % NB, g = blockIdx.x / NB;
    const int col64 = (g >> 1) * 320 + (g & 1) * 192, colh = (g >> 1) * 320 + 128;
    const uint32_t sb = SB0 + ((blockIdx.x & 1) << 24);

    if (threadIdx.x == 416) {
        if (b < 20) { tma_prefetch_2d(&map_wq, g * NSTEP * DH, b * 32); tma_prefetch_2d(&map_wq, g * NSTEP * DH + 64, b * 32); }
        asm volatile("prefetch.tensormap [%0];" :: "l"((uint64_t)&map_wq) : "memory");
        asm volatile("prefetch.tensormap [%0];" :: "l"((uint64_t)&map_k) : "memory");
        asm volatile("prefetch.tensormap [%0];" :: "l"((uint64_t)&map_v) : "memory");
        asm volatile("prefetch.tensormap [%0];" :: "l"((uint64_t)&map_wo) : "memory");
    }
    if (threadIdx.x == 448) {
        for (int i = 0; i < B_SLOTS; i++) { mbar_init(sb + BAR_BQF + 8 * i, 1); mbar_init(sb + BAR_BOF + 8 * i, 1); mbar_init(sb + BAR_BE + 8 * i, 4); }
        fence_async_smem();
        for (int i = 0; i < B_SLOTS; i++) {
            mbar_expect_tx(sb + BAR_BQF + 8 * i, TILE);
            tma_2d(sb + OFF_B + i * TILE, &map_x, i * 64, b * SQ, sb + BAR_BQF + 8 * i);
        }
        for (int i = B_SLOTS + g; i < DM / 64; i += NG) tma_prefetch_2d(&map_x, i * 64, b * SQ);
    }
    if (threadIdx.x == 0) {
        if (smem_u32(smem_raw) != sb) __trap();
        for (int i = 0; i < KV_SLOTS; i++) { mbar_init(sb + BAR_KVF + 8 * i, 1); mbar_init(sb + BAR_KVE + 8 * i, 4); }
        mbar_init(sb + BAR_QF, 4); mbar_init(sb + BAR_QE, 4); mbar_init(sb + BAR_OF, 4); mbar_init(sb + BAR_GO, 1);
    }
    if (threadIdx.x == 32) {
        for (int i = 0; i < W_SLOTS; i++) { mbar_init(sb + BAR_WQF + 8 * i, 1); mbar_init(sb + BAR_WOF + 8 * i, 1); mbar_init(sb + BAR_WE + 8 * i, 8); }
        asm volatile("fence.mbarrier_init.release.cluster;" ::: "memory");
    }
    if (threadIdx.x >= 128 && threadIdx.x < 128 + 104) {
        const int r = threadIdx.x - 128;
        asm volatile("st.shared.v4.u32 [%0], {%1, %1, %2, %2};" :: "r"(sb + OFF_REFB + 16 * r), "r"(r < 96 ? 0u : 0x3f803f80u), "r"(0u) : "memory");
    }
    if (threadIdx.x >= 256 && threadIdx.x < 256 + 10) asm volatile("st.shared.u32 [%0], %1;" :: "r"(sb + OFF_CNT + 4 * (threadIdx.x - 256)), "r"(0u) : "memory");
    fence_async_smem();
    __syncthreads();
    asm volatile("barrier.cluster.arrive.relaxed.aligned;" ::: "memory");

    if (wg == 0) {
        asm volatile("setmaxnreg.inc.sync.aligned.u32 208;");
        cluster_wait();
        const uint32_t st_off = store_offset();
        float o0[48], o1[48], s[48], l[24];
        Ring kv{0, 0};

        auto issue_s = [&](int with_ref) {
            const uint32_t ka = (SB0 + OFF_KV + kv.slot * KV_BYTES) >> 4;
            wg_fence();
            if (with_ref) mma<0, 0, 8>(s, (SB0 + OFF_ONES) >> 4, (SB0 + OFF_REFB) >> 4, 0);
#pragma unroll
            for (int k = 0; k < 8; k++)
                mma<0>(s, ka + (k >> 2) * 512 + (k & 3) * 2, ((SB0 + OFF_Q + (k >> 2) * TILE) >> 4) + (k & 3) * 2, k > 0 ? 1 : with_ref);
            wg_commit();
        };
        auto issue_pv = [&](uint32_t pbuf, int vslot, int acc, int k0, int k1) {
            const uint32_t va = (SB0 + OFF_KV + vslot * KV_BYTES) >> 4, pa = (pbuf & 0xffffff) >> 4;
            wg_fence();
#pragma unroll
            for (int k = k0; k < k1; k++) {
                mma<1>(o0, va + k * 128, pa + k * 2, k > 0 ? 1 : acc);
                mma<1>(o1, va + 512 + k * 128, pa + k * 2, k > 0 ? 1 : acc);
            }
            wg_commit();
        };
        auto softmax_store = [&](uint32_t pbuf, int first, int vprev, bool raise) {
#pragma unroll
            for (int n = 0; n < 6; n++) {
                if (n == PRI_ON) sts_pri(sb, raise, 1);
                if (PVSPLIT && n == 1 && !first) issue_pv(pbuf ^ (OFF_P ^ (OFF_P + TILE)), vprev, 1, PVSPLIT, 4);
                if (n == VREL && !first) { wg_wait<0>(); warp_arrive(sb + BAR_KVE + 8 * vprev); }
#pragma unroll
                for (int j = 8 * n; j < 8 * n + 8; j++) s[j] = ex2v(s[j]);
                stsm_t(pbuf + st_off + n * 2048, pack_bf16(s[8 * n], s[8 * n + 1]), pack_bf16(s[8 * n + 2], s[8 * n + 3]),
                       pack_bf16(s[8 * n + 4], s[8 * n + 5]), pack_bf16(s[8 * n + 6], s[8 * n + 7]));
            }
#pragma unroll
            for (int j = 0; j < 12; j++) { l[2 * j] += s[4 * j] + s[4 * j + 2]; l[2 * j + 1] += s[4 * j + 1] + s[4 * j + 3]; }
        };
        auto block = [&](uint32_t pbuf, int first, int vprev, bool pri, int tag) -> int {
            Ring vr = kv;
            ring_next<KV_SLOTS>(vr);
            const bool k_ok = mbar_test(sb + BAR_KVF + 8 * kv.slot, kv.phase), v_ok = mbar_test(sb + BAR_KVF + 8 * vr.slot, vr.phase);
            softmax_store(pbuf, first, vprev, pri && k_ok);
            if (tag) TCD(0, tag + 1);
            if (VREL == 6 && !first) { wg_wait<0>(); warp_arrive(sb + BAR_KVE + 8 * vprev); }
            if (tag) TCD(0, tag + 2);
            fence_async_smem();
            bar_sync(1);
            if (tag) TCD(0, tag + 3);
            if (!k_ok) WAITACC(mbar_wait(sb + BAR_KVF + 8 * kv.slot, kv.phase));
            issue_s(1);
            if (PRI_OFF == 0) sts_pri(sb, pri, 0);
            const int kslot = kv.slot;
            kv = vr;
            if (!v_ok) WAITACC(mbar_wait(sb + BAR_KVF + 8 * kv.slot, kv.phase));
            if (tag) TCD(0, tag + 4);
            issue_pv(pbuf, kv.slot, !first, 0, PVSPLIT ? PVSPLIT : 4);
            ring_next<KV_SLOTS>(kv);
            if (PRI_OFF == 1) sts_pri(sb, pri, 0);
            if (tag) TCD(0, tag + 5);
            wg_wait<1>();
            if (PRI_OFF == 2) sts_pri(sb, pri, 0);
            warp_arrive(sb + BAR_KVE + 8 * kslot);
            return vr.slot;
        };

        mbar_wait(sb + BAR_KVF, 0);
        mbar_wait(sb + BAR_QF, 0);
        issue_s(0);
        wg_wait<0>();
#pragma unroll 1
        for (int i = 0; i < NSTEP; i++) {
            kv.slot = uniform(kv.slot);
            kv.phase = uniform(kv.phase);
            const int idx0 = 12 * (lane >> 4) + 6 * ((lane >> 3) & 1) + 3 * ((lane >> 2) & 1);
            float c[3];
            TL(0, 4 * i);
            TC(0, 40 + i);
            warp_arrive(sb + BAR_KVE + 8 * kv.slot);
            ring_next<KV_SLOTS>(kv);
#pragma unroll
            for (int j = 0; j < 12; j++) { l[2 * j] = fmaxf(s[4 * j], s[4 * j + 2]); l[2 * j + 1] = fmaxf(s[4 * j + 1], s[4 * j + 3]); }
            column_reduce<true>(l, c, lane);
            bool bad = false;
#pragma unroll
            for (int u = 0; u < 3; u++) {
                bad |= !(fabsf(c[u]) <= REF_LIMIT);
                const int idx = idx0 + u;
                asm volatile("st.shared.u16 [%0], %1;" :: "r"(sb + OFF_REFB + 16 * (8 * (idx >> 1) + 2 * (lane & 3) + (idx & 1)) + 2 * warp),
                             "h"((unsigned short)pack_bf16(-0.125f * c[u], 0.f)) : "memory");
            }
#pragma unroll
            for (int j = 0; j < 24; j++) l[j] = 0.f;
            fence_async_smem();
            bar_sync(1);
            wg_fence();
            mma<0, 0, 8>(s, (SB0 + OFF_ONES) >> 4, (SB0 + OFF_REFB) >> 4, 1);
            wg_commit();
            wg_wait<0>();
            TLD(0, 4 * i + 1);
            const bool pri = i >= PRI_FROM && tid == 0;
            int vslot = block(sb + OFF_P, 1, 0, pri, 0);
#pragma unroll 1
            for (int j = 1; j < 7; j++) {
                if (i == 5) TCD(0, 64 + j * 10);
                vslot = block(sb + OFF_P + (j & 1) * TILE, 0, vslot, pri, i == 5 ? 64 + j * 10 : 0);
                if (i == 5) TCD(0, 64 + j * 10 + 9);
            }
            const bool v_ok = mbar_test(sb + BAR_KVF + 8 * kv.slot, kv.phase);
            softmax_store(sb + OFF_P + TILE, 0, vslot, PRI_LAST && i == NSTEP - 1 && tid == 0 && v_ok);
            if (VREL == 6) { wg_wait<0>(); warp_arrive(sb + BAR_KVE + 8 * vslot); }
#pragma unroll
            for (int j = 0; j < 24; j++) bad |= !(l[j] <= SUM_LIMIT);
            fence_async_smem();
            bad = uniform(bar_or(2, bad));
            if (!bad) warp_arrive(sb + BAR_QE);
            if (!v_ok) WAITACC(mbar_wait(sb + BAR_KVF + 8 * kv.slot, kv.phase));
            issue_pv(sb + OFF_P + TILE, kv.slot, 1, 0, 4);
            vslot = kv.slot;
            ring_next<KV_SLOTS>(kv);
            if (i == NSTEP - 1) TL(0, 4 * i + 2);
            if (i == 5) TCD(0, 150);
            column_reduce<false>(l, c, lane);
#pragma unroll
            for (int u = 0; u < 3; u++) sts_f(sb + OFF_RED + warp * 384 + 4 * (24 * (lane & 3) + idx0 + u), c[u]);
            bar_sync(1);
            if (tid < SQ) {
                const uint32_t ra = sb + OFF_RED + 4 * tid;
                sts_f(sb + OFF_INV + 4 * tid, 1.f / ((lds_f(ra) + lds_f(ra + 384)) + (lds_f(ra + 768) + lds_f(ra + 1152))));
            } else if (tid <= SQ + NG) {
                cnt_wait(sb + OFF_CNT + (tid < SQ + NG ? 16 + 4 * (tid - SQ) : 4 * g), tid < SQ + NG ? i - 1 : i);
            }
            bar_sync(1);
            if (i == 5) TCD(0, 151);
            uint8_t* og = g_oscr + (size_t)((i & 1) * NCTA + blockIdx.x) * 2 * TILE;
            auto next_scores = [&]() {
                if (i + 1 < NSTEP) {
                    WAITACC(mbar_wait(sb + BAR_KVF + 8 * kv.slot, kv.phase));
                    mbar_wait(sb + BAR_QF, (i + 1) & 1);
                }
                if (i == 5) TCD(0, 152);
                issue_s(0);
            };
            auto publish = [&]() {
                warp_arrive(sb + BAR_OF);
                if (i == NSTEP - 1 && tid == 0) {
                    const unsigned base = __float_as_uint(lds_f(sb + OFF_CNT + 32));
                    mbar_wait(sb + BAR_OF, (NSTEP - 1) & 1);
                    asm volatile("fence.proxy.async.global;" ::: "memory");
                    flag_set(&g_prog[blockIdx.x * 32], base + NSTEP);
                    TL(3, 7);
                }
                __syncwarp();
            };
            if (!bad) {
                static_for<6>([&](auto nc) {
                    constexpr int n = decltype(nc)::value;
                    const float4 r = lds_f4<OFF_INV + 16 * n>(sb + 96 * (lane & 3));
                    l[4 * n] = r.x; l[4 * n + 1] = r.y; l[4 * n + 2] = r.z; l[4 * n + 3] = r.w;
                });
                next_scores();
                if (i == 5) TCD(0, 153);
                wg_wait<1>();
                if (i == 5) TCD(0, 154);
                warp_arrive(sb + BAR_KVE + 8 * vslot);
                uint32_t* op = reinterpret_cast<uint32_t*>(og + warp * 3072) + lane;
#pragma unroll
                for (int j = 0; j < 12; j++) {
                    op[32 * j] = pack_bf16(o0[4 * j] * l[2 * j], o0[4 * j + 1] * l[2 * j + 1]);
                    op[32 * j + 384] = pack_bf16(o0[4 * j + 2] * l[2 * j], o0[4 * j + 3] * l[2 * j + 1]);
                }
#pragma unroll
                for (int j = 0; j < 12; j++) {
                    op[32 * j + 3072] = pack_bf16(o1[4 * j] * l[2 * j], o1[4 * j + 1] * l[2 * j + 1]);
                    op[32 * j + 3456] = pack_bf16(o1[4 * j + 2] * l[2 * j], o1[4 * j + 3] * l[2 * j + 1]);
                }
                if (PRI_LAST) sts_pri(sb, i == NSTEP - 1 && tid == 0, 0);
                if (i == 5) TCD(0, 155);
                TL(0, 4 * i + 3);
                publish();
                wg_wait<0>();
                if (i == 5) TCD(0, 156);
            } else {
                wg_wait<0>();
                if (PRI_LAST) sts_pri(sb, tid == 0, 0);
                warp_arrive(sb + BAR_KVE + 8 * vslot);
                const size_t u = (size_t)(b * NH + g * NSTEP + i) * SK * DH;
                slow_unit(sb, kc + u, vc + u, og, tid);
                warp_arrive(sb + BAR_QE);
                publish();
                next_scores();
                wg_wait<0>();
            }
            TC(0, 50 + i);
        }
    } else if (wg == 1) {
        asm volatile("setmaxnreg.dec.sync.aligned.u32 128;");
        cluster_wait();
        const uint32_t st_off = store_offset();
        float q0[48], q1[48];
        int ws = 0, bs = 0;
        uint32_t phases = 0;
#pragma unroll 1
        for (int i = 0; i < NSTEP; i++) {
            TL(1, 4 * i);
            projection_pass<DM / 32, PRI_Q>(sb, sb + BAR_WQF, sb + BAR_BQF, ws, bs, phases, 1000, lane, [&](uint32_t wa, uint32_t ba, int odd, int acc) {
                if (i == 0 && !odd) TLD(1, 100 + acc);
#pragma unroll
                for (int k = 0; k < 2; k++) {
                    mma<1>(q0, wa + k * 128, ba + odd * 4 + k * 2, k > 0 ? 1 : acc);
                    mma<1>(q1, wa + 256 + k * 128, ba + odd * 4 + k * 2, k > 0 ? 1 : acc);
                }
            });
            if (i >= 2) { ws = (ws + 16) % W_SLOTS; bs = (bs + 8) % B_SLOTS; }
            TL(1, 4 * i + 1);
#pragma unroll
            for (int j = 0; j < 48; j++) { q0[j] *= SM_SCALE_LOG2; q1[j] *= SM_SCALE_LOG2; }
            mbar_wait(sb + BAR_QE, (i & 1) ^ 1);
            store_tile_t(q0, sb + OFF_Q + st_off, 2048);
            store_tile_t(q1, sb + OFF_Q + TILE + st_off, 2048);
            fence_async_smem();
            warp_arrive(sb + BAR_QF);
            TLD(1, 4 * i + 2);
        }
    } else if (wg == 2) {
        asm volatile("setmaxnreg.inc.sync.aligned.u32 152;");
        cluster_wait();
        float c0[48], c1[48], c2[24];
        int ws = (3 * (DM / 32)) % W_SLOTS, bs = (3 * (DM / 64)) % B_SLOTS;
        uint32_t phases = 0;
#pragma unroll 1
        for (int i = 0; i < NSTEP; i++) {
            TLD(2, 4 * i);
            projection_pass<16, (PRI_FROM < NSTEP || PRI_LAST)>(sb, sb + BAR_WOF, sb + BAR_BOF, ws, bs, phases, i < NSTEP - 1 ? 1000 : 16 - W_SLOTS, lane, [&](uint32_t wa, uint32_t ba, int odd, int acc) {
                const uint32_t oa = (ba + odd * 384) | LBO_O;
                if (i == NSTEP - 1 && !odd) TLD(2, 48 + acc);
#pragma unroll
                for (int k = 0; k < 2; k++) {
                    mma<1, HI_128, HI_CORE, 1>(c0, wa + k * 128, oa + k * 192, k > 0 ? 1 : (acc | i));
                    mma<1, HI_128, HI_CORE, 1>(c1, wa + 256 + k * 128, oa + k * 192, k > 0 ? 1 : (acc | i));
                    mma48(c2, wa + 512 + k * 128, oa + (g & 1) * 48 + k * 192, k > 0 ? 1 : (acc | i));
                }
            });
            if (i == NSTEP - 2 && tid == 0) {
                asm volatile("prefetch.tensormap [%0];" :: "l"((uint64_t)&map_out) : "memory");
                asm volatile("prefetch.tensormap [%0];" :: "l"((uint64_t)&map_out48) : "memory");
            }
            if (i < NSTEP - 3) { ws = (ws + DM / 32) % W_SLOTS; bs = (bs + DM / 64) % B_SLOTS; }
            TL(2, 4 * i + 1);
        }
        const uint32_t st_off = store_offset();
        store_tile_t(c0, sb + OFF_KV + st_off, 2048);
        fence_async_smem();
        bar_sync(3);
        if (tid == 0) tma_store_2d(&map_out, col64, b * SQ, sb + OFF_KV);
        store_tile_t(c1, sb + OFF_KV + TILE + st_off, 2048);
#pragma unroll
        for (int n = 0; n < 3; n++)
            stsm_t(sb + OFF_KV + 2 * TILE + st_off + n * 2048, pack_bf16(c2[8 * n], c2[8 * n + 1]), pack_bf16(c2[8 * n + 2], c2[8 * n + 3]),
                   pack_bf16(c2[8 * n + 4], c2[8 * n + 5]), pack_bf16(c2[8 * n + 6], c2[8 * n + 7]));
        fence_async_smem();
        bar_sync(3);
        if (tid == 0) {
            tma_store_2d(&map_out, col64 + 64, b * SQ, sb + OFF_KV + TILE);
            tma_store_2d(&map_out48, colh, b * SQ + (g & 1) * 48, sb + OFF_KV + 2 * TILE);
            asm volatile("cp.async.bulk.commit_group;" ::: "memory");
            asm volatile("cp.async.bulk.wait_group.read 0;" ::: "memory");
        }
        TL(2, 40);
    } else {
        asm volatile("setmaxnreg.dec.sync.aligned.u32 24;");
        cluster_wait();
        if (warp == 0) {
            if (elect_one()) {
                mbar_wait(sb + BAR_GO, 0);
                uint64_t pol;
                asm volatile("createpolicy.fractional.L2::evict_first.b64 %0, 1.0;" : "=l"(pol));
                Ring w{0, 1}, t{0, 0};
                int landed = 0;
                int wide = 0;
                const int row0 = (b * NH + g * NSTEP) * SK;
                auto chunk = [&](int c) {
                    if (c < 0 || c >= NSTEP * 16) return;
                    const int r = c & 15;
                    const bool is_v = (r == 15) || (r > 0 && !(r & 1));
                    const int blk = is_v ? (r == 15 ? 7 : (r >> 1) - 1) : ((r + 1) >> 1);
                    const int win = c <= KVW1 ? 1 : KVLO + wide;
#pragma unroll 1
                    while (landed <= c - win) { mbar_wait(sb + BAR_KVF + 8 * t.slot, t.phase); ring_next<KV_SLOTS>(t); landed++; }
                    mbar_wait(sb + BAR_KVE + 8 * w.slot, w.phase);
                    TL2(c);
                    mbar_expect_tx(sb + BAR_KVF + 8 * w.slot, KV_BYTES);
                    tma_3d_hint(sb + OFF_KV + w.slot * KV_BYTES, is_v ? &map_v : &map_k, 0, row0 + (c >> 4) * SK + blk * 64, 0, sb + BAR_KVF + 8 * w.slot, pol);
                    ring_next<KV_SLOTS>(w);
                };
#pragma unroll 1
                for (int cp = 0; cp < NSTEP * 16 + 8; cp += 4) {
                    const int c = cp - KVSTAG * g;
                    chunk(c);
                    unsigned rank;
                    asm volatile("atom.relaxed.gpu.global.inc.u32 %0, [%1], %2;" : "=r"(rank) : "l"(g_kvrank + cp * 8), "n"(NCTA - 1) : "memory");
                    chunk(c + 1);
                    chunk(c + 2);
                    float rf;
                    asm volatile("cvt.rn.f32.u32 %0, %1;" : "=f"(rf) : "r"(rank));
                    wide = rf >= (float)KVRHI && cp >= 8;
                    chunk(c + 3);
                }
            }
        } else if (warp == 1) {
            const int rank = b & 1;
            if (elect_one()) {
                auto load_wq = [&](uint32_t dst, uint32_t bar, int col, int row, int odd) {
                    tma_2d_mc(dst + rank * 4096, &map_wq, col + rank * 64, row, bar);
                };
                auto load_wo = [&](uint32_t dst, uint32_t bar, int row, int odd) {
                    tma_2d_mc(dst + rank * 4096, &map_wo, col64 + rank * 64, row, bar);
                    tma_2d_mc(dst + 8192 + rank * 2048, &map_wo16, colh, row + rank * 16, bar);
                };
                Ring w{0, 1};
#pragma unroll 1
                for (int ph = 0; ph < NSTEP + 2; ph++) {
                    if (ph < NSTEP) {
#pragma unroll 1
                        for (int h = 0; h < DM / 32; h++) {
                            mbar_wait(sb + BAR_WE + 8 * w.slot, w.phase);
                            mbar_expect_tx(sb + BAR_WQF + 8 * w.slot, 8192);
                            load_wq(sb + OFF_W + w.slot * W_BYTES, sb + BAR_WQF + 8 * w.slot, (g * NSTEP + ph) * DH, h * 32, h & 1);
                            if (ph == 0) TLD(3, 200 + h);
                            ring_next<W_SLOTS>(w);
                            if (h == 4) {
                                if (ph == 0) mbar_arrive(sb + BAR_GO);
                                if (ph + 1 < NSTEP && b < 20 && (ph == 0 || ph > WPF)) {
                                    tma_prefetch_2d(&map_wq, (g * NSTEP + ph + 1) * DH, b * 32);
                                    tma_prefetch_2d(&map_wq, (g * NSTEP + ph + 1) * DH + 64, b * 32);
                                }
                                if (ph >= 1 && ph > WPF) l2_prefetch(wo + (size_t)((g * NSTEP + ph - 1) * DH + 4 * b) * DM, 4 * DM * 2);
                                if (ph == NSTEP - 1 && WPF < NSTEP) l2_prefetch(wo + (size_t)((g * NSTEP + ph) * DH + 4 * b) * DM, 4 * DM * 2);
                            }
                        }
                    }
                    if (ph >= 2) {
#pragma unroll 1
                        for (int h = 0; h < 16; h++) {
                            mbar_wait(sb + BAR_WE + 8 * w.slot, w.phase);
                            mbar_expect_tx(sb + BAR_WOF + 8 * w.slot, W_BYTES);
                            load_wo(sb + OFF_W + w.slot * W_BYTES, sb + BAR_WOF + 8 * w.slot, ((h >> 2) * NSTEP + ph - 2) * DH + (h & 3) * 32, h & 1);
                            ring_next<W_SLOTS>(w);
                        }
                    }
                }
            }
        } else if (warp == 2) {
            if (elect_one()) {
                unsigned base = 0;
                Ring a{0, 0};
                int pub = -1;
#pragma unroll 1
                for (int ph = 0; ph < NSTEP + 2; ph++) {
                    if (ph < NSTEP) {
#pragma unroll 1
                        for (int st = ph == 0 ? B_SLOTS : 0; st < DM / 64; st++) {
                            mbar_wait(sb + BAR_BE + 8 * a.slot, a.phase);
                            mbar_expect_tx(sb + BAR_BQF + 8 * a.slot, TILE);
                            tma_2d(sb + OFF_B + a.slot * TILE, &map_x, st * 64, b * SQ, sb + BAR_BQF + 8 * a.slot);
                            if (ph == 0) TLD(3, 230 + st);
                            ring_next<B_SLOTS>(a);
                            if (--pub == 0) flag_set_relaxed(&g_cons[blockIdx.x * 32], base + ph - 2);
                        }
                        if (ph == 0) base = g_prog[blockIdx.x * 32];
                    }
                    if (ph >= 2) {
#pragma unroll 1
                        for (int st = 0; st < 8; st++) {
                            const int src = (st >> 1) * NB + b;
                            if (ph > NSTEP && !(st & 1)) flag_wait(&g_prog[src * 32], base + NSTEP);
                            mbar_wait(sb + BAR_BE + 8 * a.slot, a.phase);
                            mbar_expect_tx(sb + BAR_BOF + 8 * a.slot, TILE);
                            if (--pub == 0) flag_set_relaxed(&g_cons[blockIdx.x * 32], base + ph - 2);
                            if (ph <= NSTEP && !(st & 1)) cnt_wait(sb + OFF_CNT + 4 * (st >> 1), ph - 1);
                            bulk_load(sb + OFF_B + a.slot * TILE, g_oscr + (size_t)(((ph & 1) * NCTA + src) * 2 + (st & 1)) * TILE, TILE, sb + BAR_BOF + 8 * a.slot);
                            if (ph == NSTEP + 1) TLD(3, 16 + st);
                            ring_next<B_SLOTS>(a);
                        }
                        pub = B_SLOTS;
                    }
                }
            }
        } else if (lane < 9) {
            if (WPF > 0 && lane == 0) {
                mbar_wait(sb + BAR_KVF + 8 * WPFAT, 0);
#pragma unroll 1
                for (int k = 0; k < WPF; k++) {
                    l2_prefetch(wo + (size_t)((g * NSTEP + k) * DH + 4 * b) * DM, 4 * DM * 2);
                    if (k + 2 < NSTEP && b < 20) {
                        tma_prefetch_2d(&map_wq, (g * NSTEP + k + 2) * DH, b * 32);
                        tma_prefetch_2d(&map_wq, (g * NSTEP + k + 2) * DH + 64, b * 32);
                    }
                    __nanosleep(WPFNS);
                }
            }
            __syncwarp(0x1ff);
            const unsigned base = g_prog[blockIdx.x * 32];
            const unsigned* p = (lane < 4 ? g_prog : g_cons) + ((lane & 3) * NB + b) * 32;
            const int last = lane < 4 || lane == 8 ? NSTEP - 1 : NSTEP - 2;
            if (lane == g) sts_f(sb + OFF_CNT + 32, __uint_as_float(base));
            int seen = 0;
            for (unsigned c = 0; seen < last; c++) {
                if (lane < 8) {
                    unsigned v;
                    asm volatile("ld.acquire.gpu.global.u32 %0, [%1];" : "=r"(v) : "l"(p) : "memory");
                    const int d = (int)(v - base);
                    if (d > seen) { seen = d; asm volatile("st.release.cta.shared.u32 [%0], %1;" :: "r"(sb + OFF_CNT + 4 * lane), "r"(d) : "memory"); }
                } else if (mbar_test(sb + BAR_OF, seen & 1)) {
                    asm volatile("fence.proxy.async.global;" ::: "memory");
                    flag_set(&g_prog[blockIdx.x * 32], base + ++seen);
                }
                __nanosleep(POLLNS);
                if (c > 0x1000000u) __trap();
            }
        }
    }
}

typedef CUresult (*EncodeFn)(CUtensorMap*, CUtensorMapDataType, cuuint32_t, void*, const cuuint64_t*, const cuuint64_t*,
                             const cuuint32_t*, const cuuint32_t*, CUtensorMapInterleave, CUtensorMapSwizzle,
                             CUtensorMapL2promotion, CUtensorMapFloatOOBfill);

CUtensorMap make_map(EncodeFn fn, const void* base, int rank, const cuuint64_t* dims, const cuuint64_t* strides,
                     const cuuint32_t* box, CUtensorMapSwizzle sw, CUtensorMapL2promotion promo) {
    CUtensorMap m;
    const cuuint32_t es[3] = {1, 1, 1};
    fn(&m, CU_TENSOR_MAP_DATA_TYPE_BFLOAT16, rank, const_cast<void*>(base), dims, strides, box, es,
       CU_TENSOR_MAP_INTERLEAVE_NONE, sw, promo, CU_TENSOR_MAP_FLOAT_OOB_FILL_NONE);
    return m;
}

}

extern "C" void kernel_launch(void* const* d_in, const int* in_sizes, int n_in, void* d_out, int out_size) {
    const __nv_bfloat16* x = (const __nv_bfloat16*)d_in[0];
    const __nv_bfloat16* kc = (const __nv_bfloat16*)d_in[1];
    const __nv_bfloat16* vc = (const __nv_bfloat16*)d_in[2];
    const __nv_bfloat16* wq = (const __nv_bfloat16*)d_in[3];
    const __nv_bfloat16* wo = (const __nv_bfloat16*)d_in[4];

    void* p = nullptr;
    cudaDriverEntryPointQueryResult qr;
    cudaGetDriverEntryPoint("cuTensorMapEncodeTiled", &p, cudaEnableDefault, &qr);
    EncodeFn fn = (EncodeFn)p;
    cudaFuncSetAttribute(fused_attn_kernel, cudaFuncAttributeMaxDynamicSharedMemorySize, SMEM_BYTES);

    const auto S128 = CU_TENSOR_MAP_SWIZZLE_128B;
    const auto P256 = KVPROMO, P128 = CU_TENSOR_MAP_L2_PROMOTION_L2_128B;
    const cuuint64_t dx[2] = {DM, NB * SQ}, sx[1] = {DM * 2};
    const cuuint32_t bx[2] = {64, SQ}, bx48[2] = {64, 48};
    const cuuint64_t dkv[3] = {64, (cuuint64_t)NB * NH * SK, 2}, skv[2] = {DH * 2, 128};
    const cuuint64_t dwq[2] = {NH * DH, DM}, swq[1] = {NH * DH * 2};
    const cuuint32_t b3[3] = {64, 64, 2};
    const cuuint64_t dwo[2] = {DM, NH * DH};
    const cuuint32_t bwo[2] = {64, 32}, bwo16[2] = {64, 16};

    fused_attn_kernel<<<NCTA, 512, SMEM_BYTES>>>(
        make_map(fn, x, 2, dx, sx, bx, S128, P128), make_map(fn, kc, 3, dkv, skv, b3, S128, P256),
        make_map(fn, vc, 3, dkv, skv, b3, S128, P256), make_map(fn, wq, 2, dwq, swq, bwo, S128, P128),
        make_map(fn, wo, 2, dwo, sx, bwo, S128, P128), make_map(fn, wo, 2, dwo, sx, bwo16, S128, P128),
        make_map(fn, d_out, 2, dx, sx, bx, S128, P128), make_map(fn, d_out, 2, dx, sx, bx48, S128, P128),
        x, kc, vc, wq, wo);
}
```

```cpp
#include <cuda_runtime.h>
#include <cuda.h>
#include <cuda_bf16.h>
#include <stdint.h>
#include <type_traits>

namespace {

constexpr int NB = 32, SQ = 96, DM = 640, NH = 32, SK = 512, DH = 128;
constexpr int NG = 4;
constexpr int NSTEP = NH / NG;
constexpr int NCTA = NB * NG;

#define KVW1 2
#define KVLO 2
#define KVRHI 104
#define KVSTAG 0x4320
#define WAITHINT 1
#define FAST6 1
#define DEFER 6
#define GATE 2

#define POLLNS 600
#define KVPROMO CU_TENSOR_MAP_L2_PROMOTION_L2_128B
#define KVS 5
#define NBS 3
#define NWG 15
constexpr int KV_SLOTS = KVS, KV_BYTES = 16384;
constexpr int TILE = 12288;
constexpr int B_SLOTS = NBS;
constexpr int W_GRAN = NWG, W_BOX = 4096;
constexpr int W_SLOTS = W_GRAN / 2 + 1;
constexpr int OFF_KV = 0;
constexpr int OFF_B = OFF_KV + KV_SLOTS * KV_BYTES;
constexpr int OFF_W = OFF_B + B_SLOTS * TILE;
constexpr int OFF_Q = OFF_W + W_GRAN * W_BOX;
constexpr int OFF_P = OFF_Q + 2 * TILE;
constexpr int OFF_RED = OFF_P;
constexpr int OFF_REFB = OFF_P + 2 * TILE;
constexpr int OFF_ONES = OFF_REFB + 96 * 16;
constexpr int OFF_INV = OFF_ONES + 128;
constexpr int OFF_CNT = OFF_INV + 96 * 4;
constexpr int BAR_KVF = OFF_CNT + 40, BAR_KVE = BAR_KVF + 8 * KV_SLOTS;
constexpr int BAR_WQF = BAR_KVE + 8 * KV_SLOTS, BAR_WOF = BAR_WQF + 8 * W_SLOTS, BAR_WE = BAR_WOF + 8 * W_SLOTS;
constexpr int BAR_BQF = BAR_WE + 8 * W_SLOTS, BAR_BOF = BAR_BQF + 8 * B_SLOTS, BAR_BE = BAR_BOF + 8 * B_SLOTS;
constexpr int BAR_QF = BAR_BE + 8 * B_SLOTS, BAR_QE = BAR_QF + 8, BAR_OF = BAR_QE + 8, BAR_GO = BAR_OF + 8;
constexpr int SMEM_BYTES = BAR_GO + 8;
constexpr uint32_t SB0 = 1024;
static_assert(SMEM_BYTES <= 232448, "smem");

constexpr float SM_SCALE_LOG2 = 0.08838834764831845f * 1.4426950408889634f;
constexpr float SUM_LIMIT = 1.152921504606847e18f;
constexpr float REF_LIMIT = 4096.f;

__device__ __align__(1024) uint8_t g_oscr[2 * NCTA * 2 * TILE];
__device__ unsigned g_prog[NCTA * 32];
__device__ unsigned g_cons[NCTA * 32];
__device__ unsigned g_kvrank[34 * 32];

#define TL(role, idx)
#define TLT(role, idx)
#define TL2(idx)
#define TCD(role, idx)
#define TLD(role, idx)
#define WAITACC(expr) expr
#define TC(role, idx)

__device__ __forceinline__ uint32_t smem_u32(const void* p) { return (uint32_t)__cvta_generic_to_shared(p); }
__device__ __forceinline__ void mbar_init(uint32_t bar, uint32_t cnt) { asm volatile("mbarrier.init.shared::cta.b64 [%0], %1;" :: "r"(bar), "r"(cnt) : "memory"); }
__device__ __forceinline__ void mbar_expect_tx(uint32_t bar, uint32_t bytes) { asm volatile("mbarrier.arrive.expect_tx.shared::cta.b64 _, [%0], %1;" :: "r"(bar), "r"(bytes) : "memory"); }
__device__ __forceinline__ void mbar_arrive(uint32_t bar) { asm volatile("mbarrier.arrive.shared::cta.b64 _, [%0];" :: "r"(bar) : "memory"); }
__device__ __forceinline__ void mbar_wait(uint32_t bar, uint32_t parity) {
    asm volatile("{\n.reg .pred p;\n.reg .u32 c;\n"
                 "mbarrier.try_wait.parity.shared::cta.b64 p, [%0], %1;\n"
                 "@p bra LAB_DONE;\n"
                 "mov.u32 c, 0;\n"
                 "LAB_WAIT:\n"
                 "mbarrier.try_wait.parity.shared::cta.b64 p, [%0], %1, 0x4000;\n"
                 "@p bra LAB_DONE;\n"
                 "add.u32 c, c, 1;\nsetp.lt.u32 p, c, 0x100000;\n"
                 "@p bra LAB_WAIT;\n"
                 "trap;\n"
                 "LAB_DONE:\n}" :: "r"(bar), "r"(parity) : "memory");
}
__device__ __forceinline__ bool mbar_test(uint32_t bar, uint32_t parity) {
    uint32_t r;
    asm volatile("{\n.reg .pred p;\nmbarrier.test_wait.parity.shared::cta.b64 p, [%1], %2;\nselp.u32 %0, 1, 0, p;\n}" : "=r"(r) : "r"(bar), "r"(parity) : "memory");
    return r != 0;
}
__device__ __forceinline__ void warp_arrive(uint32_t bar) {
    __syncwarp();
    if ((threadIdx.x & 31) == 0) mbar_arrive(bar);
}
__device__ __forceinline__ void lane_arrive(uint32_t addr) {
    asm volatile("{\n.reg .pred p;\nsetp.ne.u32 p, %0, 0;\n@p mbarrier.arrive.shared::cluster.b64 _, [%0];\n}" :: "r"(addr) : "memory");
}
__device__ __forceinline__ void cluster_wait() { asm volatile("barrier.cluster.wait.acquire.aligned;" ::: "memory"); }
__device__ __forceinline__ void cnt_wait(uint32_t addr, int target) {
    for (unsigned c = 0;; c++) {
        int v;
        asm volatile("ld.acquire.cta.shared.u32 %0, [%1];" : "=r"(v) : "r"(addr) : "memory");
        if (v >= target) return;
        __nanosleep(64);
        if (c > 0x4000000u) __trap();
    }
}
__device__ __forceinline__ void flag_set_relaxed(unsigned* p, unsigned v) { asm volatile("st.relaxed.gpu.global.u32 [%0], %1;" :: "l"(p), "r"(v) : "memory"); }
__device__ __forceinline__ void flag_set(unsigned* p, unsigned v) { asm volatile("st.release.gpu.global.u32 [%0], %1;" :: "l"(p), "r"(v) : "memory"); }
__device__ __forceinline__ void fence_async_smem() { asm volatile("fence.proxy.async.shared::cta;" ::: "memory"); }
__device__ __forceinline__ void bar_sync(int id) { asm volatile("bar.sync %0, 128;" :: "r"(id) : "memory"); }
__device__ __forceinline__ bool bar_or(int id, bool v) {
    uint32_t r;
    asm volatile("{\n.reg .pred p, q;\nsetp.ne.u32 p, %2, 0;\nbar.red.or.pred q, %1, 128, p;\nselp.u32 %0, 1, 0, q;\n}" : "=r"(r) : "r"(id), "r"((uint32_t)v) : "memory");
    return r != 0;
}
__device__ __forceinline__ void tma_2d(uint32_t dst, const CUtensorMap* m, int c0, int c1, uint32_t bar) {
    asm volatile("cp.async.bulk.tensor.2d.shared::cluster.global.mbarrier::complete_tx::bytes [%0], [%1, {%3, %4}], [%2];"
                 :: "r"(dst), "l"((uint64_t)m), "r"(bar), "r"(c0), "r"(c1) : "memory");
}
__device__ __forceinline__ void tma_2d_mc(uint32_t dst, const CUtensorMap* m, int c0, int c1, uint32_t bar) {
    asm volatile("cp.async.bulk.tensor.2d.shared::cluster.global.mbarrier::complete_tx::bytes.multicast::cluster [%0], [%1, {%3, %4}], [%2], %5;"
                 :: "r"(dst), "l"((uint64_t)m), "r"(bar), "r"(c0), "r"(c1), "h"((uint16_t)3) : "memory");
}
__device__ __forceinline__ void tma_prefetch_2d(const CUtensorMap* m, int c0, int c1) {
    asm volatile("cp.async.bulk.prefetch.tensor.2d.L2.global [%0, {%1, %2}];" :: "l"((uint64_t)m), "r"(c0), "r"(c1) : "memory");
}
__device__ __forceinline__ void tma_3d_hint(uint32_t dst, const CUtensorMap* m, int c0, int c1, int c2, uint32_t bar, uint64_t pol) {
    asm volatile("cp.async.bulk.tensor.3d.shared::cluster.global.mbarrier::complete_tx::bytes.L2::cache_hint [%0], [%1, {%3, %4, %5}], [%2], %6;"
                 :: "r"(dst), "l"((uint64_t)m), "r"(bar), "r"(c0), "r"(c1), "r"(c2), "l"(pol) : "memory");
}
__device__ __forceinline__ void tma_store_2d(const CUtensorMap* m, int c0, int c1, uint32_t src) {
    asm volatile("cp.async.bulk.tensor.2d.global.shared::cta.bulk_group [%0, {%2, %3}], [%1];"
                 :: "l"((uint64_t)m), "r"(src), "r"(c0), "r"(c1) : "memory");
}
__device__ __forceinline__ void bulk_load(uint32_t dst, const void* src, uint32_t bytes, uint32_t bar) {
    asm volatile("cp.async.bulk.shared::cluster.global.mbarrier::complete_tx::bytes [%0], [%1], %2, [%3];"
                 :: "r"(dst), "l"((uint64_t)src), "r"(bytes), "r"(bar) : "memory");
}
__device__ __forceinline__ void l2_prefetch(const void* p, uint32_t bytes) {
    asm volatile("cp.async.bulk.prefetch.L2.global [%0], %1;" :: "l"((uint64_t)p), "r"(bytes) : "memory");
}
__device__ __forceinline__ void wg_fence() { asm volatile("wgmma.fence.sync.aligned;" ::: "memory"); }
__device__ __forceinline__ void wg_commit() { asm volatile("wgmma.commit_group.sync.aligned;" ::: "memory"); }
template <int N> __device__ __forceinline__ void wg_wait() { asm volatile("wgmma.wait_group.sync.aligned %0;" :: "n"(N) : "memory"); }
__device__ __forceinline__ float ex2v(float x) { float y; asm volatile("ex2.approx.ftz.f32 %0, %1;" : "=f"(y) : "f"(x)); return y; }
__device__ __forceinline__ uint32_t pack_bf16(float lo, float hi) { uint32_t r; asm("cvt.rn.bf16x2.f32 %0, %1, %2;" : "=r"(r) : "f"(hi), "f"(lo)); return r; }
__device__ __forceinline__ void stsm_t(uint32_t addr, uint32_t r0, uint32_t r1, uint32_t r2, uint32_t r3) {
    asm volatile("stmatrix.sync.aligned.m8n8.x4.trans.shared.b16 [%0], {%1, %2, %3, %4};" :: "r"(addr), "r"(r0), "r"(r1), "r"(r2), "r"(r3) : "memory");
}
template <int OFF> __device__ __forceinline__ float4 lds_f4(uint32_t addr) {
    float4 v;
    asm volatile("ld.shared.v4.f32 {%0, %1, %2, %3}, [%4 + %5];" : "=f"(v.x), "=f"(v.y), "=f"(v.z), "=f"(v.w) : "r"(addr), "n"(OFF) : "memory");
    return v;
}
__device__ __forceinline__ float lds_f(uint32_t addr) { float v; asm volatile("ld.shared.f32 %0, [%1];" : "=f"(v) : "r"(addr) : "memory"); return v; }
__device__ __forceinline__ void stg_if(uint32_t* p, uint32_t v, bool on) {
    asm volatile("{\n.reg .pred p;\nsetp.ne.u32 p, %2, 0;\n@p st.global.u32 [%0], %1;\n}" :: "l"(p), "r"(v), "r"((uint32_t)on) : "memory");
}
__device__ __forceinline__ void sts_f(uint32_t addr, float v) { asm volatile("st.shared.f32 [%0], %1;" :: "r"(addr), "f"(v) : "memory"); }

constexpr uint32_t HI_128 = (1u << 30) | 64u;
constexpr uint32_t HI_CORE = 8u;
constexpr uint32_t LBO_O = (1536u >> 4) << 16;
__device__ __forceinline__ uint32_t uniform(uint32_t v) { return __shfl_sync(0xffffffffu, v, 0); }
__device__ __forceinline__ bool elect_one() {
    uint32_t r;
    asm volatile("{\n.reg .pred p;\nelect.sync _|p, 0xffffffff;\nselp.u32 %0, 1, 0, p;\n}" : "=r"(r));
    return r != 0;
}

template <int TA, uint32_t HA = HI_128, uint32_t HB = HI_128, int TB = 0>
__device__ __forceinline__ void mma(float (&d)[48], uint32_t a, uint32_t b, int acc) {
    asm volatile("{\n.reg .pred p;\n.reg .b64 da, db;\nsetp.ne.b32 p, %50, 0;\n"
                 "mov.b64 da, {%48, %52};\nmov.b64 db, {%49, %53};\n"
                 "wgmma.mma_async.sync.aligned.m64n96k16.f32.bf16.bf16 "
                 "{%0, %1, %2, %3, %4, %5, %6, %7, %8, %9, %10, %11, %12, %13, %14, %15, %16, %17, %18, %19, %20, %21, %22, %23, "
                 "%24, %25, %26, %27, %28, %29, %30, %31, %32, %33, %34, %35, %36, %37, %38, %39, %40, %41, %42, %43, %44, %45, %46, %47}, "
                 "da, db, p, 1, 1, %51, %54;\n}"
                 : "+f"(d[0]), "+f"(d[1]), "+f"(d[2]), "+f"(d[3]), "+f"(d[4]), "+f"(d[5]), "+f"(d[6]), "+f"(d[7]),
                   "+f"(d[8]), "+f"(d[9]), "+f"(d[10]), "+f"(d[11]), "+f"(d[12]), "+f"(d[13]), "+f"(d[14]), "+f"(d[15]),
                   "+f"(d[16]), "+f"(d[17]), "+f"(d[18]), "+f"(d[19]), "+f"(d[20]), "+f"(d[21]), "+f"(d[22]), "+f"(d[23]),
                   "+f"(d[24]), "+f"(d[25]), "+f"(d[26]), "+f"(d[27]), "+f"(d[28]), "+f"(d[29]), "+f"(d[30]), "+f"(d[31]),
                   "+f"(d[32]), "+f"(d[33]), "+f"(d[34]), "+f"(d[35]), "+f"(d[36]), "+f"(d[37]), "+f"(d[38]), "+f"(d[39]),
                   "+f"(d[40]), "+f"(d[41]), "+f"(d[42]), "+f"(d[43]), "+f"(d[44]), "+f"(d[45]), "+f"(d[46]), "+f"(d[47])
                 : "r"(a), "r"(b), "r"(acc), "n"(TA), "n"(HA), "n"(HB), "n"(TB));
}

__device__ __forceinline__ void mma48(float (&d)[24], uint32_t a, uint32_t b, int acc) {
    asm volatile("{\n.reg .pred p;\n.reg .b64 da, db;\nsetp.ne.b32 p, %26, 0;\n"
                 "mov.b64 da, {%24, %27};\nmov.b64 db, {%25, %28};\n"
                 "wgmma.mma_async.sync.aligned.m64n48k16.f32.bf16.bf16 "
                 "{%0, %1, %2, %3, %4, %5, %6, %7, %8, %9, %10, %11, %12, %13, %14, %15, %16, %17, %18, %19, %20, %21, %22, %23}, "
                 "da, db, p, 1, 1, 1, 1;\n}"
                 : "+f"(d[0]), "+f"(d[1]), "+f"(d[2]), "+f"(d[3]), "+f"(d[4]), "+f"(d[5]), "+f"(d[6]), "+f"(d[7]),
                   "+f"(d[8]), "+f"(d[9]), "+f"(d[10]), "+f"(d[11]), "+f"(d[12]), "+f"(d[13]), "+f"(d[14]), "+f"(d[15]),
                   "+f"(d[16]), "+f"(d[17]), "+f"(d[18]), "+f"(d[19]), "+f"(d[20]), "+f"(d[21]), "+f"(d[22]), "+f"(d[23])
                 : "r"(a), "r"(b), "r"(acc), "n"(HI_128), "n"(HI_CORE));
}

__device__ __forceinline__ void store_tile_t(const float (&d)[48], uint32_t addr, int step) {
#pragma unroll
    for (int n = 0; n < 6; n++)
        stsm_t(addr + n * step, pack_bf16(d[8 * n], d[8 * n + 1]), pack_bf16(d[8 * n + 2], d[8 * n + 3]),
               pack_bf16(d[8 * n + 4], d[8 * n + 5]), pack_bf16(d[8 * n + 6], d[8 * n + 7]));
}

__device__ __forceinline__ void column_reduce(const float (&v)[24], float (&c)[3], int lane) {
    const bool b4 = lane & 16, b3 = lane & 8, b2 = lane & 4;
    float a[12], b[6];
#pragma unroll
    for (int i = 0; i < 12; i++) {
        float keep = b4 ? v[12 + i] : v[i], send = b4 ? v[i] : v[12 + i];
        float o = __shfl_xor_sync(0xffffffffu, send, 16);
        a[i] = keep + o;
    }
#pragma unroll
    for (int i = 0; i < 6; i++) {
        float keep = b3 ? a[6 + i] : a[i], send = b3 ? a[i] : a[6 + i];
        float o = __shfl_xor_sync(0xffffffffu, send, 8);
        b[i] = keep + o;
    }
#pragma unroll
    for (int i = 0; i < 3; i++) {
        float keep = b2 ? b[3 + i] : b[i], send = b2 ? b[i] : b[3 + i];
        float o = __shfl_xor_sync(0xffffffffu, send, 4);
        c[i] = keep + o;
    }
}

template <int N, class F> __device__ __forceinline__ void static_for(F&& f) {
    if constexpr (N > 0) { static_for<N - 1>(f); f(std::integral_constant<int, N - 1>{}); }
}

__device__ __forceinline__ uint32_t store_offset() {
    uint32_t t;
    asm volatile("mov.u32 %0, %%tid.x;" : "=r"(t));
    const uint32_t lane = t & 31, warp = (t >> 5) & 3;
    return ((lane >> 4) * 8 + (lane & 7)) * 128 + (((2 * warp + ((lane >> 3) & 1)) ^ (lane & 7)) << 4);
}

__device__ __forceinline__ int fresh_tid() {
    uint32_t t;
    asm volatile("mov.u32 %0, %%tid.x;" : "=r"(t));
    return t & 127;
}
__device__ __forceinline__ uint32_t max_bf16x2(uint32_t a, uint32_t b) { uint32_t r; asm("max.bf16x2 %0, %1, %2;" : "=r"(r) : "r"(a), "r"(b)); return r; }

struct Ring { int slot; uint32_t phase; };
template <int N> __device__ __forceinline__ void ring_next(Ring& r) { if (++r.slot == N) { r.slot = 0; r.phase ^= 1; } }

struct Proj {
    int ws, wg, bs;
    __device__ __forceinline__ void skip(int steps, int boxes) {
        ws = (ws + steps) % W_SLOTS; wg = (wg + steps * boxes) % W_GRAN; bs = (bs + steps / 2) % B_SLOTS;
    }
};
__device__ __forceinline__ int next_box(int g) { return g + 1 == W_GRAN ? 0 : g + 1; }

template <int NH32, int NBOX, class F>
__device__ __forceinline__ void projection_pass(uint32_t sb, uint32_t wfull, uint32_t bfull, Proj& p, uint32_t& phases,
                                                int keep_from, int lane, F&& issue) {
    const uint32_t rel_w = lane < 2 ? (SB0 + BAR_WE) + (lane << 24) : 0, rel_b = lane == 2 ? sb + BAR_BE : 0;
    uint32_t rel = 0;
    bool ok = false;
    auto landed = [&](int odd) {
        bool r = mbar_test(wfull + 8 * p.ws, (phases >> p.ws) & 1);
        if (!odd) r &= mbar_test(bfull + 8 * p.bs, (phases >> (16 + p.bs)) & 1);
        return r;
    };
#pragma unroll 1
    for (int st = 0; st < NH32 / 2; st++) {
#pragma unroll
        for (int odd = 0; odd < 2; odd++) {
            if (!ok && !landed(odd)) {
                wg_wait<0>();
                lane_arrive(rel);
                rel = 0;
                mbar_wait(wfull + 8 * p.ws, (phases >> p.ws) & 1);
                if (!odd) mbar_wait(bfull + 8 * p.bs, (phases >> (16 + p.bs)) & 1);
            }
            const int g1 = next_box(p.wg), g2 = next_box(g1);
            constexpr uint32_t w0 = (SB0 + OFF_W) >> 4;
            wg_fence();
            issue(w0 + p.wg * (W_BOX / 16), w0 + g1 * (W_BOX / 16), w0 + g2 * (W_BOX / 16), (SB0 + OFF_B + p.bs * TILE) >> 4, odd, st + odd);
            wg_commit();
            uint32_t nrel = (rel_w && 2 * st + odd < keep_from) ? rel_w + 8 * p.ws : 0;
            if (odd && rel_b) nrel = rel_b + 8 * p.bs;
            phases ^= odd ? (1u << p.ws) | (0x10000u << p.bs) : 1u << p.ws;
            if (++p.ws == W_SLOTS) p.ws = 0;
            p.wg = NBOX == 2 ? g2 : next_box(g2);
            if (odd && ++p.bs == B_SLOTS) p.bs = 0;
            ok = landed(odd ^ 1);
            wg_wait<1>();
            lane_arrive(rel);
            rel = nrel;
        }
    }
    wg_wait<0>();
    lane_arrive(rel);
}

__device__ __forceinline__ void slow_unit(uint32_t sb, const __nv_bfloat16* __restrict__ xg, const __nv_bfloat16* __restrict__ wg,
                                          const __nv_bfloat16* __restrict__ kg, const __nv_bfloat16* __restrict__ vg, uint8_t* og, int tid) {
    if (tid >= SQ) return;
    const uint32_t qrow = sb + OFF_P + tid * 256;
#pragma unroll 1
    for (int c = 0; c < 16; c++) {
        float a[8] = {0.f, 0.f, 0.f, 0.f, 0.f, 0.f, 0.f, 0.f};
#pragma unroll 1
        for (int k = 0; k < DM; k++) {
            const float xv = __bfloat162float(xg[tid * DM + k]);
            const uint4 wv = *reinterpret_cast<const uint4*>(wg + (size_t)k * (NH * DH) + c * 8);
            const uint32_t wa[4] = {wv.x, wv.y, wv.z, wv.w};
#pragma unroll
            for (int u = 0; u < 4; u++) {
                a[2 * u] = fmaf(xv, __uint_as_float(wa[u] << 16), a[2 * u]);
                a[2 * u + 1] = fmaf(xv, __uint_as_float(wa[u] & 0xffff0000u), a[2 * u + 1]);
            }
        }
        asm volatile("st.shared.v4.u32 [%0], {%1, %2, %3, %4};" :: "r"(qrow + ((c ^ (tid & 7)) << 4)), "r"(pack_bf16(a[0], a[1])),
                     "r"(pack_bf16(a[2], a[3])), "r"(pack_bf16(a[4], a[5])), "r"(pack_bf16(a[6], a[7])) : "memory");
    }
    auto score = [&](int key) {
        float s = 0.f;
#pragma unroll 1
        for (int c = 0; c < 16; c++) {
            uint4 qv, kv = *reinterpret_cast<const uint4*>(kg + key * DH + c * 8);
            asm volatile("ld.shared.v4.u32 {%0, %1, %2, %3}, [%4];" : "=r"(qv.x), "=r"(qv.y), "=r"(qv.z), "=r"(qv.w)
                         : "r"(qrow + ((c ^ (tid & 7)) << 4)) : "memory");
            const uint32_t qa[4] = {qv.x, qv.y, qv.z, qv.w}, ka[4] = {kv.x, kv.y, kv.z, kv.w};
#pragma unroll
            for (int u = 0; u < 4; u++) {
                s = fmaf(__uint_as_float(qa[u] << 16), __uint_as_float(ka[u] << 16), s);
                s = fmaf(__uint_as_float(qa[u] & 0xffff0000u), __uint_as_float(ka[u] & 0xffff0000u), s);
            }
        }
        return s;
    };
    float m = -INFINITY;
#pragma unroll 1
    for (int key = 0; key < SK; key++) m = fmaxf(m, score(key));
#pragma unroll 1
    for (int c0 = 0; c0 < 16; c0 += 2) {
        float acc[16], l = 0.f;
#pragma unroll
        for (int u = 0; u < 16; u++) acc[u] = 0.f;
#pragma unroll 1
        for (int key = 0; key < SK; key++) {
            const float p = exp2f((score(key) - m) * SM_SCALE_LOG2);
            l += p;
#pragma unroll
            for (int c = 0; c < 2; c++) {
                const uint4 vv = *reinterpret_cast<const uint4*>(vg + key * DH + (c0 + c) * 8);
                const uint32_t va[4] = {vv.x, vv.y, vv.z, vv.w};
#pragma unroll
                for (int u = 0; u < 4; u++) {
                    acc[8 * c + 2 * u] = fmaf(p, __uint_as_float(va[u] << 16), acc[8 * c + 2 * u]);
                    acc[8 * c + 2 * u + 1] = fmaf(p, __uint_as_float(va[u] & 0xffff0000u), acc[8 * c + 2 * u + 1]);
                }
            }
        }
        const float inv = 1.f / l;
#pragma unroll
        for (int u = 0; u < 16; u++)
            *reinterpret_cast<__nv_bfloat16*>(og + (c0 + (u >> 3)) * 1536 + (tid >> 3) * 128 + (u & 7) * 16 + (tid & 7) * 2) = __float2bfloat16(acc[u] * inv);
    }
}

__global__ void __cluster_dims__(2, 1, 1) __launch_bounds__(512, 1)
fused_attn_kernel(const __grid_constant__ CUtensorMap map_x, const __grid_constant__ CUtensorMap map_k,
                  const __grid_constant__ CUtensorMap map_v, const __grid_constant__ CUtensorMap map_wq,
                  const __grid_constant__ CUtensorMap map_wo, const __grid_constant__ CUtensorMap map_wo16,
                  const __grid_constant__ CUtensorMap map_out, const __grid_constant__ CUtensorMap map_out48,
                  const __nv_bfloat16* __restrict__ x, const __nv_bfloat16* __restrict__ kc, const __nv_bfloat16* __restrict__ vc,
                  const __nv_bfloat16* __restrict__ wq, const __nv_bfloat16* __restrict__ wo) {
    extern __shared__ __align__(1024) uint8_t smem_raw[];
    const int tid = threadIdx.x & 127, wg = uniform(threadIdx.x >> 7), lane = tid & 31;
    const int b = blockIdx.x % NB, g = blockIdx.x / NB;
    const int col64 = (g >> 1) * 320 + (g & 1) * 192, colh = (g >> 1) * 320 + 128;
    const uint32_t sb = SB0 + ((blockIdx.x & 1) << 24);

    if (threadIdx.x == 416) {
        if (b < 20) { tma_prefetch_2d(&map_wq, g * NSTEP * DH, b * 32); tma_prefetch_2d(&map_wq, g * NSTEP * DH + 64, b * 32); }
        asm volatile("prefetch.tensormap [%0];" :: "l"((uint64_t)&map_wq) : "memory");
        asm volatile("prefetch.tensormap [%0];" :: "l"((uint64_t)&map_k) : "memory");
        asm volatile("prefetch.tensormap [%0];" :: "l"((uint64_t)&map_v) : "memory");
        asm volatile("prefetch.tensormap [%0];" :: "l"((uint64_t)&map_wo) : "memory");
    }
    if (threadIdx.x == 448) {
        for (int i = 0; i < B_SLOTS; i++) { mbar_init(sb + BAR_BQF + 8 * i, 1); mbar_init(sb + BAR_BOF + 8 * i, 1); mbar_init(sb + BAR_BE + 8 * i, 4); }
        fence_async_smem();
        for (int i = 0; i < B_SLOTS; i++) {
            mbar_expect_tx(sb + BAR_BQF + 8 * i, TILE);
            tma_2d(sb + OFF_B + i * TILE, &map_x, i * 64, b * SQ, sb + BAR_BQF + 8 * i);
        }
        for (int i = B_SLOTS + g; i < DM / 64; i += NG) tma_prefetch_2d(&map_x, i * 64, b * SQ);
    }
    if (threadIdx.x == 0) {
        if (smem_u32(smem_raw) != sb) __trap();
        for (int i = 0; i < KV_SLOTS; i++) { mbar_init(sb + BAR_KVF + 8 * i, 1); mbar_init(sb + BAR_KVE + 8 * i, 4); }
        mbar_init(sb + BAR_QF, 4); mbar_init(sb + BAR_QE, 4); mbar_init(sb + BAR_OF, 4); mbar_init(sb + BAR_GO, 1);
    }
    if (threadIdx.x == 32) {
        for (int i = 0; i < W_SLOTS; i++) { mbar_init(sb + BAR_WQF + 8 * i, 1); mbar_init(sb + BAR_WOF + 8 * i, 1); mbar_init(sb + BAR_WE + 8 * i, 8); }
        asm volatile("fence.mbarrier_init.release.cluster;" ::: "memory");
    }
    if (threadIdx.x >= 128 && threadIdx.x < 128 + 104) {
        const int r = threadIdx.x - 128;
        asm volatile("st.shared.v4.u32 [%0], {%1, %1, %2, %2};" :: "r"(sb + OFF_REFB + 16 * r), "r"(r < 96 ? 0u : 0xbe00be00u), "r"(0u) : "memory");
    }
    if (threadIdx.x >= 256 && threadIdx.x < 256 + 8) asm volatile("st.shared.u32 [%0], %1;" :: "r"(sb + OFF_CNT + 4 * (threadIdx.x - 256)), "r"(0u) : "memory");
    fence_async_smem();
    __syncthreads();
    asm volatile("barrier.cluster.arrive.relaxed.aligned;" ::: "memory");

    if (wg == 0) {
        asm volatile("setmaxnreg.inc.sync.aligned.u32 208;");
        cluster_wait();
        const uint32_t st_off = store_offset();
        float o0[48], o1[48], s[48], l[24];
        Ring kv{0, 0};

        auto issue_s = [&](int kslot, int with_ref) {
            const uint32_t ka = (SB0 + OFF_KV + kslot * KV_BYTES) >> 4;
            wg_fence();
            if (with_ref) mma<0, 0, 8>(s, (SB0 + OFF_ONES) >> 4, (SB0 + OFF_REFB) >> 4, 0);
#pragma unroll
            for (int k = 0; k < 8; k++)
                mma<0>(s, ka + (k >> 2) * 512 + (k & 3) * 2, ((SB0 + OFF_Q + (k >> 2) * TILE) >> 4) + (k & 3) * 2, k > 0 ? 1 : with_ref);
            wg_commit();
        };
        auto issue_pv = [&](uint32_t pbuf, int vslot, int acc, int k0, int k1) {
            const uint32_t va = (SB0 + OFF_KV + vslot * KV_BYTES) >> 4, pa = (pbuf & 0xffffff) >> 4;
            wg_fence();
#pragma unroll
            for (int k = k0; k < k1; k++) {
                mma<1>(o0, va + k * 128, pa + k * 2, k > 0 ? 1 : acc);
                mma<1>(o1, va + 512 + k * 128, pa + k * 2, k > 0 ? 1 : acc);
            }
            wg_commit();
        };
        auto store_o = [&](uint32_t* op, int n, bool on) {
#pragma unroll
            for (int j = 2 * n; j < 2 * n + 2; j++) {
                stg_if(op + 32 * j, pack_bf16(o0[4 * j], o0[4 * j + 1]), on);
                stg_if(op + 32 * j + 384, pack_bf16(o0[4 * j + 2], o0[4 * j + 3]), on);
                stg_if(op + 32 * j + 3072, pack_bf16(o1[4 * j], o1[4 * j + 1]), on);
                stg_if(op + 32 * j + 3456, pack_bf16(o1[4 * j + 2], o1[4 * j + 3]), on);
            }
        };
        uint32_t pk[24];
        auto softmax_store = [&](uint32_t pbuf, int first, int vprev, uint32_t* op, bool on) {
#pragma unroll
            for (int n = 0; n < 6; n++) {
                if (n == 1 && !first) issue_pv(pbuf ^ (OFF_P ^ (OFF_P + TILE)), vprev, 1, 2, 4);
#pragma unroll
                for (int j = 8 * n; j < 8 * n + 8; j++) s[j] = ex2v(s[j]);
#pragma unroll
                for (int j = 4 * n; j < 4 * n + 4; j++) pk[j] = pack_bf16(s[2 * j], s[2 * j + 1]);
                stsm_t(pbuf + st_off + n * 2048, pk[4 * n], pk[4 * n + 1], pk[4 * n + 2], pk[4 * n + 3]);
                if (first == 2) store_o(op, n, on);
                if (n < 6 - DEFER) {
#pragma unroll
                    for (int j = 2 * n; j < 2 * n + 2; j++) {
                        l[2 * j] = first ? s[4 * j] + s[4 * j + 2] : l[2 * j] + (s[4 * j] + s[4 * j + 2]);
                        l[2 * j + 1] = first ? s[4 * j + 1] + s[4 * j + 3] : l[2 * j + 1] + (s[4 * j + 1] + s[4 * j + 3]);
                    }
                }
            }
        };
        auto add_sums = [&](int first, uint32_t zero) {
#pragma unroll
            for (int j = 2 * (6 - DEFER); j < 12; j++) {
                float a0, a1, b0, b1;
                asm volatile("prmt.b32 %0, %4, %6, 0x1044;\nprmt.b32 %1, %4, %6, 0x3244;\nprmt.b32 %2, %5, %6, 0x1044;\nprmt.b32 %3, %5, %6, 0x3244;"
                             : "=f"(a0), "=f"(a1), "=f"(b0), "=f"(b1) : "r"(pk[2 * j]), "r"(pk[2 * j + 1]), "r"(zero));
                l[2 * j] = first ? a0 + b0 : l[2 * j] + (a0 + b0);
                l[2 * j + 1] = first ? a1 + b1 : l[2 * j + 1] + (a1 + b1);
            }
        };
        auto block = [&](uint32_t pbuf, int first, int vprev, uint32_t* op, bool on) -> int {
            Ring vr = kv;
            ring_next<KV_SLOTS>(vr);
            const bool k_ok = mbar_test(sb + BAR_KVF + 8 * kv.slot, kv.phase), v_ok = mbar_test(sb + BAR_KVF + 8 * vr.slot, vr.phase);
            softmax_store(pbuf, first, vprev, op, on);
            if (!k_ok) WAITACC(mbar_wait(sb + BAR_KVF + 8 * kv.slot, kv.phase));
            issue_s(kv.slot, 1);
            if (!first) { wg_wait<1>(); warp_arrive(sb + BAR_KVE + 8 * vprev); }
            if (first == 2) warp_arrive(sb + BAR_OF);
            uint32_t zero;
            asm volatile("ld.volatile.shared.u32 %0, [%1];" : "=r"(zero) : "r"(sb + OFF_ONES + 8) : "memory");
            add_sums(first, zero);
            fence_async_smem();
            bar_sync(1);
            const int kslot = kv.slot;
            kv = vr;
            if (!v_ok) WAITACC(mbar_wait(sb + BAR_KVF + 8 * kv.slot, kv.phase));
            issue_pv(pbuf, kv.slot, !first, 0, 2);
            ring_next<KV_SLOTS>(kv);
            wg_wait<1>();
            warp_arrive(sb + BAR_KVE + 8 * kslot);
            return vr.slot;
        };
        auto write_max = [&]() {
            const int tid = fresh_tid(), lane = tid & 31, warp = tid >> 5;
            const bool b4 = lane & 16, b3 = lane & 8, b2 = lane & 4;
            uint32_t m[12], a[6], c[3];
#pragma unroll
            for (int j = 0; j < 12; j++) m[j] = pack_bf16(fmaxf(s[4 * j], s[4 * j + 2]), fmaxf(s[4 * j + 1], s[4 * j + 3]));
#pragma unroll
            for (int j = 0; j < 6; j++) a[j] = max_bf16x2(b4 ? m[6 + j] : m[j], __shfl_xor_sync(0xffffffffu, b4 ? m[j] : m[6 + j], 16));
#pragma unroll
            for (int j = 0; j < 3; j++) c[j] = max_bf16x2(b3 ? a[3 + j] : a[j], __shfl_xor_sync(0xffffffffu, b3 ? a[j] : a[3 + j], 8));
#pragma unroll
            for (int j = 0; j < 3; j++) {
                c[j] = max_bf16x2(c[j], __shfl_xor_sync(0xffffffffu, c[j], 4));
                const uint32_t v = b2 ? c[j] & 0xffff0000u : c[j] << 16;
                asm volatile("st.shared.u16 [%0], %1;" :: "r"(sb + OFF_REFB + 16 * (8 * (3 * (lane >> 3) + j) + 2 * (lane & 3) + b2) + 2 * warp),
                             "h"((unsigned short)(fabsf(__uint_as_float(v)) <= REF_LIMIT ? v >> 16 : 0x7fffu)) : "memory");
            }
        };
        auto apply_refs = [&]() {
            wg_fence();
            mma<0, 0, 8>(s, (SB0 + OFF_ONES) >> 4, (SB0 + OFF_REFB) >> 4, 1);
            wg_commit();
        };
        auto write_sums = [&]() {
            const int tid = fresh_tid(), lane = tid & 31, warp = tid >> 5, idx0 = 12 * (lane >> 4) + 6 * ((lane >> 3) & 1) + 3 * ((lane >> 2) & 1);
            float c[3];
            column_reduce(l, c, lane);
#pragma unroll
            for (int u = 0; u < 3; u++) sts_f(sb + OFF_RED + warp * 384 + 4 * (24 * (lane & 3) + idx0 + u), c[u]);
        };
        auto invert_sums = [&](int i) {
            const int tid = fresh_tid(), lane = tid & 31;
            if (tid < SQ) {
                const uint32_t ra = sb + OFF_RED + 4 * tid;
                sts_f(sb + OFF_INV + 4 * tid, 1.f / ((lds_f(ra) + lds_f(ra + 384)) + (lds_f(ra + 768) + lds_f(ra + 1152))));
            } else if (tid <= SQ + NG) {
                cnt_wait(sb + OFF_CNT + (tid < SQ + NG ? 16 + 4 * (tid - SQ) : 4 * g), tid < SQ + NG ? i - 1 : i);
            }
            bar_sync(1);
            static_for<6>([&](auto nc) {
                constexpr int n = decltype(nc)::value;
                const float4 r = lds_f4<OFF_INV + 16 * n>(sb + 96 * (lane & 3));
                l[4 * n] = r.x; l[4 * n + 1] = r.y; l[4 * n + 2] = r.z; l[4 * n + 3] = r.w;
            });
        };
        auto o_ptr = [&](uint8_t* og) { const int t = fresh_tid(); return reinterpret_cast<uint32_t*>(og + (t >> 5) * 3072) + (t & 31); };
        auto overflowed = [&]() {
            bool bad = false;
#pragma unroll
            for (int j = 0; j < 24; j++) bad |= !(l[j] <= SUM_LIMIT);
            return bad;
        };
        auto normalize = [&]() {
#pragma unroll
            for (int j = 0; j < 48; j++) { o0[j] *= l[2 * (j >> 2) + (j & 1)]; o1[j] *= l[2 * (j >> 2) + (j & 1)]; }
        };
        auto redo_head = [&](int i, uint8_t* og) {
            const int h = g * NSTEP + i;
            const size_t u = (size_t)(b * NH + h) * SK * DH;
            bar_sync(1);
            slow_unit(sb, x + (size_t)b * SQ * DM, wq + h * DH, kc + u, vc + u, og, fresh_tid());
            bar_sync(1);
        };

        mbar_wait(sb + BAR_KVF, 0);
        mbar_wait(sb + BAR_QF, 0);
        issue_s(0, 0);
        wg_wait<0>();
        TL(0, 0);
        TC(0, 40);
        warp_arrive(sb + BAR_KVE);
        ring_next<KV_SLOTS>(kv);
        write_max();
        fence_async_smem();
        bar_sync(1);
        apply_refs();
        wg_wait<0>();
        int vslot = block(sb + OFF_P, 1, 0, nullptr, false);
#pragma unroll 1
        for (int i = 0;; i++) {
#pragma unroll 1
            for (int j = 1; j < 7; j++) vslot = block(sb + OFF_P + (j & 1) * TILE, 0, vslot, nullptr, false);
            warp_arrive(sb + BAR_QE);
            softmax_store(sb + OFF_P + TILE, 0, vslot, nullptr, false);
            if (i == NSTEP - 1) break;
            Ring vr = kv;
            ring_next<KV_SLOTS>(vr);
            WAITACC(mbar_wait(sb + BAR_KVF + 8 * kv.slot, kv.phase));
            mbar_wait(sb + BAR_QF, (i + 1) & 1);
            issue_s(kv.slot, 0);
            wg_wait<1>();
            warp_arrive(sb + BAR_KVE + 8 * vslot);
            add_sums(0, __float_as_uint(lds_f(sb + OFF_ONES + 8)));
            fence_async_smem();
            const bool redo = uniform(bar_or(2, overflowed()));
            WAITACC(mbar_wait(sb + BAR_KVF + 8 * vr.slot, vr.phase));
            issue_pv(sb + OFF_P + TILE, vr.slot, 1, 0, 2);
            write_sums();
            issue_pv(sb + OFF_P + TILE, vr.slot, 1, 2, 4);
            wg_wait<2>();
            TL(0, 4 * i + 3);
            TC(0, 50 + i);
            TL(0, 4 * i + 4);
            TC(0, 41 + i);
            warp_arrive(sb + BAR_KVE + 8 * kv.slot);
            write_max();
            fence_async_smem();
            bar_sync(1);
            apply_refs();
            invert_sums(i);
            wg_wait<0>();
            warp_arrive(sb + BAR_KVE + 8 * vr.slot);
            ring_next<KV_SLOTS>(vr);
            kv.slot = uniform(vr.slot);
            kv.phase = uniform(vr.phase);
            uint8_t* og = g_oscr + (size_t)((i & 1) * NCTA + blockIdx.x) * 2 * TILE;
            normalize();
            if (redo) redo_head(i, og);
            vslot = block(sb + OFF_P, 2, 0, o_ptr(og), !redo);
        }
        {
            wg_wait<0>();
            fence_async_smem();
            bar_sync(1);
            WAITACC(mbar_wait(sb + BAR_KVF + 8 * kv.slot, kv.phase));
            issue_pv(sb + OFF_P + TILE, kv.slot, 1, 0, 4);
            TL(0, 30);
            add_sums(0, __float_as_uint(lds_f(sb + OFF_ONES + 8)));
            const bool bad = overflowed();
            write_sums();
            const bool redo = uniform(bar_or(2, bad));
            invert_sums(NSTEP - 1);
            wg_wait<0>();
            uint8_t* og = g_oscr + (size_t)(((NSTEP - 1) & 1) * NCTA + blockIdx.x) * 2 * TILE;
            uint32_t* op = o_ptr(og);
            normalize();
#pragma unroll
            for (int n = 0; n < 6; n++) store_o(op, n, !redo);
            if (redo) redo_head(NSTEP - 1, og);
            TL(0, 31);
            TC(0, 57);
            warp_arrive(sb + BAR_OF);
            if (tid == 0) {
                const unsigned base = __float_as_uint(lds_f(sb + OFF_CNT + 32));
                mbar_wait(sb + BAR_OF, (NSTEP - 1) & 1);
                asm volatile("fence.proxy.async.global;" ::: "memory");
                flag_set(&g_prog[blockIdx.x * 32], base + NSTEP);
                TL(3, 7);
            }
        }
    } else if (wg == 1) {
        asm volatile("setmaxnreg.dec.sync.aligned.u32 128;");
        cluster_wait();
        const uint32_t st_off = store_offset();
        float q0[48], q1[48];
        Proj p{0, 0, 0};
        uint32_t phases = 0;
#pragma unroll 1
        for (int i = 0; i < NSTEP; i++) {
            TL(1, 4 * i);
            projection_pass<DM / 32, 2>(sb, sb + BAR_WQF, sb + BAR_BQF, p, phases, 1000, lane, [&](uint32_t wa, uint32_t wb, uint32_t, uint32_t ba, int odd, int acc) {
                if (i == 0 && !odd) TLD(1, 100 + acc);
#pragma unroll
                for (int k = 0; k < 2; k++) {
                    mma<1>(q0, wa + k * 128, ba + odd * 4 + k * 2, k > 0 ? 1 : acc);
                    mma<1>(q1, wb + k * 128, ba + odd * 4 + k * 2, k > 0 ? 1 : acc);
                }
            });
            if (i >= 2) p.skip(16, 3);
            TL(1, 4 * i + 1);
#pragma unroll
            for (int j = 0; j < 48; j++) { q0[j] *= SM_SCALE_LOG2; q1[j] *= SM_SCALE_LOG2; }
            mbar_wait(sb + BAR_QE, (i & 1) ^ 1);
            store_tile_t(q0, sb + OFF_Q + st_off, 2048);
            store_tile_t(q1, sb + OFF_Q + TILE + st_off, 2048);
            fence_async_smem();
            warp_arrive(sb + BAR_QF);
            TLD(1, 4 * i + 2);
        }
        if (FAST6 && tid == 0) {
            cnt_wait(sb + OFF_CNT + 4 * g, NSTEP - 2);
            const unsigned base = __float_as_uint(lds_f(sb + OFF_CNT + 32));
            mbar_wait(sb + BAR_OF, (NSTEP - 2) & 1);
            asm volatile("fence.proxy.async.global;" ::: "memory");
            flag_set(&g_prog[blockIdx.x * 32], base + NSTEP - 1);
        }
    } else if (wg == 2) {
        asm volatile("setmaxnreg.inc.sync.aligned.u32 152;");
        cluster_wait();
        float c0[48], c1[48], c2[24];
        Proj p{0, 0, 0};
        p.skip(3 * (DM / 32), 2);
        uint32_t phases = 0;
#pragma unroll 1
        for (int i = 0; i < NSTEP; i++) {
            TLD(2, 4 * i);
            if (GATE && i == NSTEP - 1) mbar_wait(sb + (GATE == 1 ? BAR_QE : BAR_OF), (NSTEP - 1) & 1);
            projection_pass<16, 3>(sb, sb + BAR_WOF, sb + BAR_BOF, p, phases, i < NSTEP - 1 ? 1000 : 16 - W_GRAN / 3, lane,
                                   [&](uint32_t wa, uint32_t wb, uint32_t wc, uint32_t ba, int odd, int acc) {
                const uint32_t oa = (ba + odd * 384) | LBO_O;
                if (i == NSTEP - 1) TLT(2, 48 + 2 * acc - odd);
#pragma unroll
                for (int k = 0; k < 2; k++) {
                    mma<1, HI_128, HI_CORE, 1>(c0, wa + k * 128, oa + k * 192, k > 0 ? 1 : (acc | i));
                    mma<1, HI_128, HI_CORE, 1>(c1, wb + k * 128, oa + k * 192, k > 0 ? 1 : (acc | i));
                    mma48(c2, wc + k * 128, oa + (g & 1) * 48 + k * 192, k > 0 ? 1 : (acc | i));
                }
            });
            if (i == NSTEP - 2 && tid == 0) {
                asm volatile("prefetch.tensormap [%0];" :: "l"((uint64_t)&map_out) : "memory");
                asm volatile("prefetch.tensormap [%0];" :: "l"((uint64_t)&map_out48) : "memory");
            }
            if (i < NSTEP - 3) p.skip(DM / 32, 2);
            TL(2, 4 * i + 1);
        }
        const uint32_t st_off = store_offset();
        store_tile_t(c0, sb + OFF_KV + st_off, 2048);
        fence_async_smem();
        bar_sync(3);
        if (tid == 0) tma_store_2d(&map_out, col64, b * SQ, sb + OFF_KV);
        store_tile_t(c1, sb + OFF_KV + TILE + st_off, 2048);
#pragma unroll
        for (int n = 0; n < 3; n++)
            stsm_t(sb + OFF_KV + 2 * TILE + st_off + n * 2048, pack_bf16(c2[8 * n], c2[8 * n + 1]), pack_bf16(c2[8 * n + 2], c2[8 * n + 3]),
                   pack_bf16(c2[8 * n + 4], c2[8 * n + 5]), pack_bf16(c2[8 * n + 6], c2[8 * n + 7]));
        fence_async_smem();
        bar_sync(3);
        if (tid == 0) {
            tma_store_2d(&map_out, col64 + 64, b * SQ, sb + OFF_KV + TILE);
            tma_store_2d(&map_out48, colh, b * SQ + (g & 1) * 48, sb + OFF_KV + 2 * TILE);
            asm volatile("cp.async.bulk.commit_group;" ::: "memory");
            asm volatile("cp.async.bulk.wait_group.read 0;" ::: "memory");
        }
        TL(2, 40);
    } else {
        asm volatile("setmaxnreg.dec.sync.aligned.u32 24;");
        const int warp = uniform(fresh_tid() >> 5);
        cluster_wait();
        if (warp == 0) {
            if (elect_one()) {
                mbar_wait(sb + BAR_GO, 0);
                uint64_t pol;
                asm volatile("createpolicy.fractional.L2::evict_first.b64 %0, 1.0;" : "=l"(pol));
                Ring w{0, 1}, t{0, 0};
                int landed = 0;
                int wide = 0;
                const int row0 = (b * NH + g * NSTEP) * SK;
                auto chunk = [&](int c) {
                    if (c < 0 || c >= NSTEP * 16) return;
                    const bool is_v = c == NSTEP * 16 - 1 || (c > 0 && !(c & 1));
                    const int blk = is_v ? (c - 1) >> 1 : (c + 1) >> 1;
                    const int win = c <= KVW1 ? 1 : KVLO + wide;
#pragma unroll 1
                    while (landed <= c - win) { mbar_wait(sb + BAR_KVF + 8 * t.slot, t.phase); ring_next<KV_SLOTS>(t); landed++; }
                    mbar_wait(sb + BAR_KVE + 8 * w.slot, w.phase);
                    TL2(c);
                    mbar_expect_tx(sb + BAR_KVF + 8 * w.slot, KV_BYTES);
                    tma_3d_hint(sb + OFF_KV + w.slot * KV_BYTES, is_v ? &map_v : &map_k, 0, row0 + blk * 64, 0, sb + BAR_KVF + 8 * w.slot, pol);
                    ring_next<KV_SLOTS>(w);
                };
#pragma unroll 1
                for (int cp = 0; cp < NSTEP * 16 + 8; cp += 4) {
                    const int c = cp - ((KVSTAG >> (4 * g)) & 15);
                    chunk(c);
                    unsigned rank;
                    asm volatile("atom.relaxed.gpu.global.inc.u32 %0, [%1], %2;" : "=r"(rank) : "l"(g_kvrank + cp * 8), "n"(NCTA - 1) : "memory");
                    chunk(c + 1);
                    chunk(c + 2);
                    float rf;
                    asm volatile("cvt.rn.f32.u32 %0, %1;" : "=f"(rf) : "r"(rank));
                    wide = rf >= (float)KVRHI && cp >= 8;
                    chunk(c + 3);
                }
            }
        } else if (warp == 1) {
            const int rank = b & 1;
            if (elect_one()) {
                int ws = 0, wg = 0, room = W_GRAN;
                uint32_t sizes = 0;
                Ring t{0, 0};
                auto reserve = [&](int n) {
#pragma unroll 1
                    while (room < n) {
                        mbar_wait(sb + BAR_WE + 8 * t.slot, t.phase);
                        room += 2 + ((sizes >> t.slot) & 1);
                        ring_next<W_SLOTS>(t);
                    }
                    room -= n;
                    sizes = (sizes & ~(1u << ws)) | ((n - 2) << ws);
                };
#pragma unroll 1
                for (int ph = 0; ph < NSTEP + 2; ph++) {
                    if (ph < NSTEP) {
#pragma unroll 1
                        for (int h = 0; h < DM / 32; h++) {
                            reserve(2);
                            const int g1 = next_box(wg);
                            mbar_expect_tx(sb + BAR_WQF + 8 * ws, 2 * W_BOX);
                            tma_2d_mc(sb + OFF_W + (rank ? g1 : wg) * W_BOX, &map_wq, (g * NSTEP + ph) * DH + rank * 64, h * 32, sb + BAR_WQF + 8 * ws);
                            if (ph == 0) TLD(3, 200 + h);
                            wg = next_box(g1);
                            if (++ws == W_SLOTS) ws = 0;
                            if (h == 4) {
                                if (ph == 0) mbar_arrive(sb + BAR_GO);
                                if (ph + 1 < NSTEP && b < 20) {
                                    tma_prefetch_2d(&map_wq, (g * NSTEP + ph + 1) * DH, b * 32);
                                    tma_prefetch_2d(&map_wq, (g * NSTEP + ph + 1) * DH + 64, b * 32);
                                }
                                if (ph >= 1) l2_prefetch(wo + (size_t)((g * NSTEP + ph - 1) * DH + 4 * b) * DM, 4 * DM * 2);
                                if (ph == NSTEP - 1) l2_prefetch(wo + (size_t)((g * NSTEP + ph) * DH + 4 * b) * DM, 4 * DM * 2);
                            }
                        }
                    }
                    if (ph >= 2) {
#pragma unroll 1
                        for (int h = 0; h < 16; h++) {
                            reserve(3);
                            const int g1 = next_box(wg), g2 = next_box(g1), row = ((h >> 2) * NSTEP + ph - 2) * DH + (h & 3) * 32;
                            mbar_expect_tx(sb + BAR_WOF + 8 * ws, 3 * W_BOX);
                            tma_2d_mc(sb + OFF_W + (rank ? g1 : wg) * W_BOX, &map_wo, col64 + rank * 64, row, sb + BAR_WOF + 8 * ws);
                            tma_2d_mc(sb + OFF_W + g2 * W_BOX + rank * 2048, &map_wo16, colh, row + rank * 16, sb + BAR_WOF + 8 * ws);
                            if (ph == NSTEP + 1) TLT(3, 32 + h);
                            wg = next_box(g2);
                            if (++ws == W_SLOTS) ws = 0;
                        }
                    }
                }
            }
        } else if (warp == 2) {
            if (elect_one()) {
                unsigned base = 0;
                Ring a{0, 0};
                int ready = 0;
                int pub = -1;
#pragma unroll 1
                for (int ph = 0; ph < NSTEP + 2; ph++) {
                    if (ph < NSTEP) {
#pragma unroll 1
                        for (int st = ph == 0 ? B_SLOTS : 0; st < DM / 64; st++) {
                            mbar_wait(sb + BAR_BE + 8 * a.slot, a.phase);
                            mbar_expect_tx(sb + BAR_BQF + 8 * a.slot, TILE);
                            tma_2d(sb + OFF_B + a.slot * TILE, &map_x, st * 64, b * SQ, sb + BAR_BQF + 8 * a.slot);
                            if (ph == 0) TLD(3, 230 + st);
                            ring_next<B_SLOTS>(a);
                            if (--pub == 0) flag_set_relaxed(&g_cons[blockIdx.x * 32], base + ph - 2);
                        }
                        if (ph == 0) base = g_prog[blockIdx.x * 32];
                    }
                    if (ph >= 2) {
#pragma unroll 1
                        for (int st = 0; st < 8; st++) {
                            const int src = (st >> 1) * NB + b;
                            if (st == 0) ready = 0;
                            if (ph > NSTEP - FAST6) {
                                for (unsigned c = 0; !((ready >> (st >> 1)) & 1); c++) {
                                    unsigned v[NG];
#pragma unroll
                                    for (int k = 0; k < NG; k++) asm volatile("ld.relaxed.gpu.global.u32 %0, [%1];" : "=r"(v[k]) : "l"(&g_prog[(k * NB + b) * 32]) : "memory");
                                    asm volatile("fence.acq_rel.cta;" ::: "memory");
#pragma unroll
                                    for (int k = 0; k < NG; k++) ready |= ((int)(v[k] - base) >= ph - 1) << k;
                                    if (c > 0x1000000u) __trap();
                                }
                            }
                            mbar_wait(sb + BAR_BE + 8 * a.slot, a.phase);
                            mbar_expect_tx(sb + BAR_BOF + 8 * a.slot, TILE);
                            if (--pub == 0) flag_set_relaxed(&g_cons[blockIdx.x * 32], base + ph - 2);
                            if (ph <= NSTEP - FAST6 && !(st & 1)) cnt_wait(sb + OFF_CNT + 4 * (st >> 1), ph - 1);
                            bulk_load(sb + OFF_B + a.slot * TILE, g_oscr + (size_t)(((ph & 1) * NCTA + src) * 2 + (st & 1)) * TILE, TILE, sb + BAR_BOF + 8 * a.slot);
                            if (ph == NSTEP + 1) TLT(3, 16 + st);
                            ring_next<B_SLOTS>(a);
                        }
                        pub = B_SLOTS;
                    }
                }
            }
        } else if (lane < 9) {
            const unsigned base = g_prog[blockIdx.x * 32];
            const unsigned* p = (lane < 4 ? g_prog : g_cons) + ((lane & 3) * NB + b) * 32;
            const int last = lane < 4 ? NSTEP - 1 : lane < 8 ? NSTEP - 2 : NSTEP - 1 - FAST6;
            if (lane == g) sts_f(sb + OFF_CNT + 32, __uint_as_float(base));
            int seen = 0;
            for (unsigned c = 0; seen < last; c++) {
                if (lane < 8) {
                    unsigned v;
                    asm volatile("ld.acquire.gpu.global.u32 %0, [%1];" : "=r"(v) : "l"(p) : "memory");
                    const int d = (int)(v - base);
                    if (d > seen) { seen = d; asm volatile("st.release.cta.shared.u32 [%0], %1;" :: "r"(sb + OFF_CNT + 4 * lane), "r"(d) : "memory"); }
                } else if (mbar_test(sb + BAR_OF, seen & 1)) {
                    asm volatile("fence.proxy.async.global;" ::: "memory");
                    flag_set(&g_prog[blockIdx.x * 32], base + ++seen);
                }
                __nanosleep(POLLNS);
                if (c > 0x1000000u) __trap();
            }
        }
    }
}

typedef CUresult (*EncodeFn)(CUtensorMap*, CUtensorMapDataType, cuuint32_t, void*, const cuuint64_t*, const cuuint64_t*,
                             const cuuint32_t*, const cuuint32_t*, CUtensorMapInterleave, CUtensorMapSwizzle,
                             CUtensorMapL2promotion, CUtensorMapFloatOOBfill);

CUtensorMap make_map(EncodeFn fn, const void* base, int rank, const cuuint64_t* dims, const cuuint64_t* strides,
                     const cuuint32_t* box, CUtensorMapSwizzle sw, CUtensorMapL2promotion promo) {
    CUtensorMap m;
    const cuuint32_t es[3] = {1, 1, 1};
    fn(&m, CU_TENSOR_MAP_DATA_TYPE_BFLOAT16, rank, const_cast<void*>(base), dims, strides, box, es,
       CU_TENSOR_MAP_INTERLEAVE_NONE, sw, promo, CU_TENSOR_MAP_FLOAT_OOB_FILL_NONE);
    return m;
}

}

extern "C" void kernel_launch(void* const* d_in, const int* in_sizes, int n_in, void* d_out, int out_size) {
    const __nv_bfloat16* x = (const __nv_bfloat16*)d_in[0];
    const __nv_bfloat16* kc = (const __nv_bfloat16*)d_in[1];
    const __nv_bfloat16* vc = (const __nv_bfloat16*)d_in[2];
    const __nv_bfloat16* wq = (const __nv_bfloat16*)d_in[3];
    const __nv_bfloat16* wo = (const __nv_bfloat16*)d_in[4];

    void* p = nullptr;
    cudaDriverEntryPointQueryResult qr;
    cudaGetDriverEntryPoint("cuTensorMapEncodeTiled", &p, cudaEnableDefault, &qr);
    EncodeFn fn = (EncodeFn)p;
    cudaFuncSetAttribute(fused_attn_kernel, cudaFuncAttributeMaxDynamicSharedMemorySize, SMEM_BYTES);

    const auto S128 = CU_TENSOR_MAP_SWIZZLE_128B;
    const auto P256 = KVPROMO, P128 = CU_TENSOR_MAP_L2_PROMOTION_L2_128B;
    const cuuint64_t dx[2] = {DM, NB * SQ}, sx[1] = {DM * 2};
    const cuuint32_t bx[2] = {64, SQ}, bx48[2] = {64, 48};
    const cuuint64_t dkv[3] = {64, (cuuint64_t)NB * NH * SK, 2}, skv[2] = {DH * 2, 128};
    const cuuint64_t dwq[2] = {NH * DH, DM}, swq[1] = {NH * DH * 2};
    const cuuint32_t b3[3] = {64, 64, 2};
    const cuuint64_t dwo[2] = {DM, NH * DH};
    const cuuint32_t bwo[2] = {64, 32}, bwo16[2] = {64, 16};

    fused_attn_kernel<<<NCTA, 512, SMEM_BYTES>>>(
        make_map(fn, x, 2, dx, sx, bx, S128, P128), make_map(fn, kc, 3, dkv, skv, b3, S128, P256),
        make_map(fn, vc, 3, dkv, skv, b3, S128, P256), make_map(fn, wq, 2, dwq, swq, bwo, S128, P128),
        make_map(fn, wo, 2, dwo, sx, bwo, S128, P128), make_map(fn, wo, 2, dwo, sx, bwo16, S128, P128),
        make_map(fn, d_out, 2, dx, sx, bx, S128, P128), make_map(fn, d_out, 2, dx, sx, bx48, S128, P128),
        x, kc, vc, wq, wo);
}
```
